```python
import torch

def _softmax(x, axis=-1):
    return torch.softmax(x, dim=axis)
def _gelu(x):
    return torch.nn.functional.gelu(x, approximate="tanh")
def _silu(x):
    return torch.nn.functional.silu(x)
def _sigmoid(x):
    return torch.sigmoid(x)
def _layernorm(x, axis=-1, eps=1e-5):
    m = x.mean(dim=axis, keepdim=True)
    v = x.var(dim=axis, keepdim=True, unbiased=False)
    return (x - m) / torch.sqrt(v + eps)
def _scatter_add(tgt, idx, src, axis=0):
    return tgt.clone().index_add_(axis, idx, src)
def _segment_sum(src, seg, n):
    out = torch.zeros((n,) + src.shape[1:], dtype=src.dtype)
    return out.index_add_(0, seg, src)
def _pad(x, pw):
    flat = tuple(v for pair in reversed(pw) for v in pair)
    return torch.nn.functional.pad(x, flat)

kernel_name = 'gated_mix__spectral_fnet__glu_gated_glu__prompt'

def setup_inputs():

    _w = (lambda a: (lambda t: t.to(torch.bfloat16) if t.is_floating_point() else t)(torch.as_tensor(a)))
    def _A_setup():
        B, S, D = 1, 2048, 1024
        ns = torch.arange(S)[:, None] * torch.arange(S)[None, :]
        nd = torch.arange(D)[:, None] * torch.arange(D)[None, :]
        Ws_re = torch.cos(-2.0 * torch.pi * ns / S).to(float)
        Ws_im = torch.sin(-2.0 * torch.pi * ns / S).to(float)
        Wd_re = torch.cos(-2.0 * torch.pi * nd / D).to(float)
        Wd_im = torch.sin(-2.0 * torch.pi * nd / D).to(float)
        return {
            "x": _w((lambda *s: torch.randn(*s, dtype=torch.bfloat16) * 0.05)(B, S, D)),
            "dft_seq_re": _w(Ws_re),
            "dft_seq_im": _w(Ws_im),
            "dft_hid_re": _w(Wd_re),
            "dft_hid_im": _w(Wd_im),
        }
    _A_in = _A_setup()

    def _B_setup():
        B, S, D, F = 1, 2048, 1024, 3584
        return {
            "x": _w((lambda *s: torch.randn(*s, dtype=torch.bfloat16) * 0.05)(B, S, D)),
            "w_gate": _w((lambda *s: torch.randn(*s, dtype=torch.bfloat16) * 1.6)(D, F)),
            "w_up": _w((lambda *s: torch.randn(*s, dtype=torch.bfloat16) * 0.8)(D, F)),
            "w_down": _w((lambda *s: torch.randn(*s, dtype=torch.bfloat16) * 0.8)(F, D)),
        }
    _B_in = _B_setup()

    return {
        "A_x": _A_in["x"],
        "A_dft_seq_re": _A_in["dft_seq_re"],
        "A_dft_seq_im": _A_in["dft_seq_im"],
        "A_dft_hid_re": _A_in["dft_hid_re"],
        "A_dft_hid_im": _A_in["dft_hid_im"],
        "B_x": _B_in["x"],
        "B_w_gate": _B_in["w_gate"],
        "B_w_up": _B_in["w_up"],
        "B_w_down": _B_in["w_down"],
        "gate_w": _w((lambda *s: torch.randn(*s, dtype=torch.bfloat16) * 0.05)(1024) * 16.0),
    }

def reference(A_x, A_dft_seq_re, A_dft_seq_im, A_dft_hid_re, A_dft_hid_im, B_x, B_w_gate, B_w_up, B_w_down, gate_w):
    def _A_ref(x, dft_seq_re, dft_seq_im, dft_hid_re, dft_hid_im):
        a = torch.einsum("bsd,ed->bse", x, dft_hid_re)
        b = torch.einsum("bsd,ed->bse", x, dft_hid_im)
        y = torch.einsum("ts,bse->bte", dft_seq_re, a) - torch.einsum("ts,bse->bte", dft_seq_im, b)
        return y

    def _B_ref(x, w_gate, w_up, w_down):
        g = torch.einsum("bsd,df->bsf", x, w_gate)
        u = torch.einsum("bsd,df->bsf", x, w_up)
        h = _sigmoid(g) * u
        return torch.einsum("bsf,fd->bsd", h, w_down)

    x = A_x
    g = _sigmoid((x * gate_w).sum(-1, keepdims=True))
    a = _A_ref(x, A_dft_seq_re, A_dft_seq_im, A_dft_hid_re, A_dft_hid_im)
    b = _B_ref(x, B_w_gate, B_w_up, B_w_down)
    return g * a + (1 - g) * b
```

```cpp
#include <cuda_runtime.h>
#include <cuda_bf16.h>
#include <cuda.h>
#include <stdint.h>

#define SCHED 0
#define MAPPING 0
#define NBETA 12

namespace {

constexpr int SEQ = 2048, DM = 1024, FF = 3584;
constexpr int KZ = 88;
constexpr int XROW0 = 16 * KZ * 128;
constexpr int ZROWS = XROW0 + 128 * 2 * 128;

constexpr int STAGES = 4;
constexpr int A_BYTES = 128 * 64 * 2, B_BYTES = 256 * 64 * 2, ST_BYTES = A_BYTES + B_BYTES;
constexpr int OFF_STG = STAGES * ST_BYTES;
constexpr int OFF_BAR = OFF_STG + 32768;
constexpr int SMEM_BYTES = OFF_BAR + 256 + 1024;
constexpr int B_FULL = 0, B_EMPTY = 32, B_SFULL = 64, B_SEMPTY = 96, B_RECV = 128, B_GDONE = 144,
              B_GREADY = 152, B_EPOCH = 160, W_EPOCH = 176;

enum { T_END = 0, T_PQ = 1, T_GU = 2, T_OUTK = 3, T_OUTM = 4, T_OUTB = 5 };
enum { E_NONE = 0, E_PQ = 1, E_GU = 2, E_HELP = 3, E_SEND = 4, E_FIN = 5, E_FINRED = 6 };

__host__ __device__ constexpr uint32_t mkseg(int type, int m, int idx, int k0, int nk, int first, int swap, int epi) {
  return (uint32_t)type | ((uint32_t)m << 3) | ((uint32_t)idx << 7) | ((uint32_t)k0 << 12) | ((uint32_t)nk << 19) |
         ((uint32_t)first << 26) | ((uint32_t)swap << 27) | ((uint32_t)epi << 28);
}
#define SEG_TYPE(s) ((s) & 7u)
#define SEG_M(s) (((s) >> 3) & 15u)
#define SEG_IDX(s) (((s) >> 7) & 31u)
#define SEG_K0(s) (((s) >> 12) & 127u)
#define SEG_NK(s) (((s) >> 19) & 127u)
#define SEG_FIRST(s) (((s) >> 26) & 1u)
#define SEG_SWAP(s) (((s) >> 27) & 1u)
#define SEG_EPI(s) (((s) >> 28) & 7u)

constexpr int NCTA = (SCHED == 0) ? 128 : 132;
constexpr int MAXSEG = 16;
struct Sched { uint32_t s[132][MAXSEG]; };

__host__ __device__ constexpr int blk_m(int b) { return MAPPING == 0 ? (b & 15) : (b >> 3); }
__host__ __device__ constexpr int blk_j(int b) { return MAPPING == 0 ? (b >> 4) : (b & 7); }
__host__ __device__ constexpr uint32_t first_seg(int b) {
  return b < 128 ? mkseg(T_PQ, blk_m(b), blk_j(b), 0, 32, 1, 0, E_PQ)
                 : mkseg(T_GU, (b - 128) * 4, 26, 0, 16, 1, 0, E_GU);
}

constexpr Sched make_sched() {
  Sched t{};
  for (int b = 0; b < 128; b++) {
    int m = blk_m(b), j = blk_j(b), c = 0;
    t.s[b][c++] = first_seg(b);
    for (int r = 0; r < 3; r++) t.s[b][c++] = mkseg(T_GU, m, r * 8 + j, 0, 16, 1, 0, E_GU);
    int n = j >> 1;
    const int nb = NBETA, a_odd = 36 - nb / 2, a_even = 20 - nb / 2;
    if (j & 1) {
      t.s[b][c++] = mkseg(T_GU, m, 24 + n, 0, 16, 1, 0, E_GU);
      t.s[b][c++] = mkseg(T_OUTM, m, n, 32, a_odd, 1, 1, E_SEND);
      t.s[b][c++] = mkseg(T_OUTB, m, n, KZ - nb, nb, 0, 1, E_FIN);
    } else {
      t.s[b][c++] = mkseg(T_OUTK, m, n, 0, 32, 1, 0, E_NONE);
      t.s[b][c++] = mkseg(T_OUTM, m, n, 32 + a_odd, a_even, 0, 0, E_SEND);
      t.s[b][c++] = mkseg(T_OUTB, m, n, KZ - nb, nb, 0, 0, E_FIN);
    }
  }
  return t;
}
__constant__ Sched c_sched = make_sched();

struct Params {
  CUtensorMap sre, sim, xa, xb, wg, wu, hre, him, wd, zld, zst, outm;
  const uint4* x;
  const uint4* gw;
};

__device__ __align__(1024) __nv_bfloat16 g_Z[(size_t)ZROWS * 64];
__device__ float2 g_gate[SEQ];
__device__ unsigned g_flags[16 * 32];
__device__ unsigned g_xflag[256];
__device__ unsigned g_hflag[128];
__device__ unsigned g_gatecnt[1];
__device__ unsigned g_epoch[132];
#define PROF(slot)
#define PROFG(slot)

__device__ __forceinline__ uint32_t smem_u32(const void* p) { return (uint32_t)__cvta_generic_to_shared(p); }
__device__ __forceinline__ void mbar_init(uint32_t a, uint32_t c) {
  asm volatile("mbarrier.init.shared::cta.b64 [%0], %1;" ::"r"(a), "r"(c) : "memory");
}
__device__ __forceinline__ void mbar_expect(uint32_t a, uint32_t bytes) {
  asm volatile("mbarrier.arrive.expect_tx.shared::cta.b64 _, [%0], %1;" ::"r"(a), "r"(bytes) : "memory");
}
__device__ __forceinline__ void mbar_arrive(uint32_t a) {
  asm volatile("mbarrier.arrive.shared::cta.b64 _, [%0];" ::"r"(a) : "memory");
}
__device__ __forceinline__ void mbar_wait(uint32_t a, uint32_t parity) {
  asm volatile(
      "{ .reg .pred p; .reg .u32 it;\n"
      "mov.u32 it, 0;\n"
      "WAIT_LOOP:\n"
      "mbarrier.try_wait.parity.shared::cta.b64 p, [%0], %1;\n"
      "@p bra WAIT_DONE;\n"
      "add.u32 it, it, 1;\n"
      "setp.lt.u32 p, it, 0x400000;\n"
      "@p bra WAIT_LOOP;\n"
      "trap;\n"
      "WAIT_DONE:\n"
      "}" ::"r"(a), "r"(parity) : "memory");
}
__device__ __forceinline__ void trap_if(bool c) {
  asm volatile("{ .reg .pred p; setp.ne.u32 p, %0, 0; @p trap; }" ::"r"((uint32_t)c));
}
__device__ __forceinline__ unsigned ld_acquire(const unsigned* p) {
  unsigned v;
  asm volatile("ld.acquire.gpu.global.u32 %0, [%1];" : "=r"(v) : "l"(p) : "memory");
  return v;
}
__device__ __forceinline__ void red_release(unsigned* p) {
  asm volatile("red.release.gpu.global.add.u32 [%0], 1;" ::"l"(p) : "memory");
}
__device__ __forceinline__ void poll_ge(const unsigned* p, unsigned target) {
  uint32_t it = 0;
  while ((int)(ld_acquire(p) - target) < 0) {
    __nanosleep(40);
    trap_if(++it > (1u << 22));
  }
}
__device__ __forceinline__ void fence_async() { asm volatile("fence.proxy.async;" ::: "memory"); }
__device__ __forceinline__ void fence_async_smem() { asm volatile("fence.proxy.async.shared::cta;" ::: "memory"); }
__device__ __forceinline__ void tma2d(uint32_t dst, const CUtensorMap* m, int c0, int c1, uint32_t bar) {
  asm volatile("cp.async.bulk.tensor.2d.shared::cluster.global.mbarrier::complete_tx::bytes [%0], [%1, {%3, %4}], [%2];"
               ::"r"(dst), "l"(m), "r"(bar), "r"(c0), "r"(c1) : "memory");
}
__device__ __forceinline__ void tma3d(uint32_t dst, const CUtensorMap* m, int c1, int c2, uint32_t bar) {
  asm volatile("cp.async.bulk.tensor.3d.shared::cluster.global.mbarrier::complete_tx::bytes [%0], [%1, {%3, %4, %5}], [%2];"
               ::"r"(dst), "l"(m), "r"(bar), "r"(0), "r"(c1), "r"(c2) : "memory");
}
__device__ __forceinline__ void tma_store(const CUtensorMap* m, uint32_t src, int c0, int c1) {
  asm volatile("cp.async.bulk.tensor.2d.global.shared::cta.bulk_group [%0, {%2, %3}], [%1];"
               ::"l"(m), "r"(src), "r"(c0), "r"(c1) : "memory");
}
__device__ __forceinline__ void tma_red(const CUtensorMap* m, uint32_t src, int c0, int c1) {
  asm volatile("cp.reduce.async.bulk.tensor.2d.global.shared::cta.add.bulk_group [%0, {%2, %3}], [%1];"
               ::"l"(m), "r"(src), "r"(c0), "r"(c1) : "memory");
}
__device__ __forceinline__ void bulk_commit() { asm volatile("cp.async.bulk.commit_group;" ::: "memory"); }
__device__ __forceinline__ void bulk_wait_read() { asm volatile("cp.async.bulk.wait_group.read 0;" ::: "memory"); }
__device__ __forceinline__ void bulk_wait() { asm volatile("cp.async.bulk.wait_group 0;" ::: "memory"); }
__device__ __forceinline__ void prefetch_map(const CUtensorMap* m) {
  asm volatile("prefetch.tensormap [%0];" ::"l"(m) : "memory");
}
__device__ __forceinline__ bool elect_one() {
  uint32_t p;
  asm volatile("{ .reg .pred p; elect.sync _|p, 0xffffffff; selp.u32 %0, 1, 0, p; }" : "=r"(p));
  return p;
}
__device__ __forceinline__ void stsm4(uint32_t a, uint32_t r0, uint32_t r1, uint32_t r2, uint32_t r3) {
  asm volatile("stmatrix.sync.aligned.m8n8.x4.shared.b16 [%0], {%1,%2,%3,%4};" ::"r"(a), "r"(r0), "r"(r1), "r"(r2), "r"(r3) : "memory");
}
__device__ __forceinline__ void ldsm4(uint32_t a, uint32_t& r0, uint32_t& r1, uint32_t& r2, uint32_t& r3) {
  asm volatile("ldmatrix.sync.aligned.m8n8.x4.shared.b16 {%0,%1,%2,%3}, [%4];" : "=r"(r0), "=r"(r1), "=r"(r2), "=r"(r3) : "r"(a) : "memory");
}
__device__ __forceinline__ uint32_t pack2(float lo, float hi) {
  uint32_t r;
  asm("cvt.rn.bf16x2.f32 %0, %1, %2;" : "=r"(r) : "f"(hi), "f"(lo));
  return r;
}
__device__ __forceinline__ float bf_lo(uint32_t v) { return __uint_as_float(v << 16); }
__device__ __forceinline__ float bf_hi(uint32_t v) { return __uint_as_float(v & 0xffff0000u); }
__device__ __forceinline__ float ex2f(float x) { float r; asm("ex2.approx.ftz.f32 %0, %1;" : "=f"(r) : "f"(x)); return r; }
__device__ __forceinline__ float rcpf(float x) { float r; asm("rcp.approx.ftz.f32 %0, %1;" : "=f"(r) : "f"(x)); return r; }

#define R8(d, i) "+f"(d[i]), "+f"(d[i + 1]), "+f"(d[i + 2]), "+f"(d[i + 3]), "+f"(d[i + 4]), "+f"(d[i + 5]), "+f"(d[i + 6]), "+f"(d[i + 7])
#define R64LO(d) R8(d, 0), R8(d, 8), R8(d, 16), R8(d, 24), R8(d, 32), R8(d, 40), R8(d, 48), R8(d, 56)
#define R64HI(d) R8(d, 64), R8(d, 72), R8(d, 80), R8(d, 88), R8(d, 96), R8(d, 104), R8(d, 112), R8(d, 120)
#define S64LO "%0,%1,%2,%3,%4,%5,%6,%7,%8,%9,%10,%11,%12,%13,%14,%15,%16,%17,%18,%19,%20,%21,%22,%23,%24,%25,%26,%27,%28,%29,%30,%31," \
              "%32,%33,%34,%35,%36,%37,%38,%39,%40,%41,%42,%43,%44,%45,%46,%47,%48,%49,%50,%51,%52,%53,%54,%55,%56,%57,%58,%59,%60,%61,%62,%63"
#define S64HI "%64,%65,%66,%67,%68,%69,%70,%71,%72,%73,%74,%75,%76,%77,%78,%79,%80,%81,%82,%83,%84,%85,%86,%87,%88,%89,%90,%91,%92,%93,%94,%95," \
              "%96,%97,%98,%99,%100,%101,%102,%103,%104,%105,%106,%107,%108,%109,%110,%111,%112,%113,%114,%115,%116,%117,%118,%119,%120,%121,%122,%123,%124,%125,%126,%127"

constexpr uint32_t DESC_HI = 0x40000040u;
__device__ __forceinline__ uint64_t mkdesc(uint32_t lo) { return ((uint64_t)DESC_HI << 32) | lo; }

template <int TB>
__device__ __forceinline__ void wgmma256(float (&d)[128], uint32_t da, uint32_t db, uint32_t acc) {
  asm volatile("{ .reg .pred p; setp.ne.b32 p, %130, 0;\n"
               "wgmma.mma_async.sync.aligned.m64n256k16.f32.bf16.bf16 {" S64LO "," S64HI "}, %128, %129, p, 1, 1, 0, %131; }"
               : R64LO(d), R64HI(d) : "l"(mkdesc(da)), "l"(mkdesc(db)), "r"(acc), "n"(TB));
}
__device__ __forceinline__ void wgmma128(float (&d)[128], uint32_t da, uint32_t db) {
  asm volatile("wgmma.mma_async.sync.aligned.m64n128k16.f32.bf16.bf16 {" S64LO "}, %64, %65, 1, 1, 1, 0, 1;"
               : R64LO(d) : "l"(mkdesc(da)), "l"(mkdesc(db)));
}
__device__ __forceinline__ void wg_fence() { asm volatile("wgmma.fence.sync.aligned;" ::: "memory"); }
__device__ __forceinline__ void wg_commit() { asm volatile("wgmma.commit_group.sync.aligned;" ::: "memory"); }
__device__ __forceinline__ void wg_wait_all(float (&d)[128]) {
  asm volatile("wgmma.wait_group.sync.aligned 0;" : R64LO(d), R64HI(d)::"memory");
}
__device__ __forceinline__ void wg_wait_lo(float (&d)[128]) {
  asm volatile("wgmma.wait_group.sync.aligned 0;" : R64LO(d)::"memory");
}

__device__ __forceinline__ void stage_done(uint32_t bar) {
  fence_async_smem();
  __syncwarp();
  if (elect_one()) mbar_arrive(bar);
}

template <int C>
__device__ __forceinline__ void gu_chunk(uint32_t (&pk)[64], float ic0, float ic1, uint32_t sa) {
  uint32_t o[4];
#pragma unroll
  for (int r = 0; r < 4; r++) {
    const uint32_t G = pk[4 * C + r], U = pk[32 + 4 * C + r];
    const float ic = (r & 1) ? ic1 : ic0;
    const float e0 = ex2f(bf_lo(G) * -1.4426950408889634f), e1 = ex2f(bf_hi(G) * -1.4426950408889634f);
    o[r] = pack2(bf_lo(U) * rcpf(fmaf(e0, ic, ic)), bf_hi(U) * rcpf(fmaf(e1, ic, ic)));
  }
  stsm4((sa + (C >> 2) * 8192) ^ ((C & 3) << 5), o[0], o[1], o[2], o[3]);
}
template <int C>
__device__ __forceinline__ void plain_chunk(uint32_t (&pk)[64], uint32_t sa) {
#pragma unroll
  for (int jj = 0; jj < 4; jj++)
    stsm4((sa + (C & 1) * 8192) ^ (jj << 5), pk[16 * C + 4 * jj], pk[16 * C + 4 * jj + 1], pk[16 * C + 4 * jj + 2], pk[16 * C + 4 * jj + 3]);
}

__device__ __forceinline__ void do_chunk(int chunk, uint32_t (&pk)[64], float s0, float s1, uint32_t sa, uint32_t sbar, uint32_t sph) {
  switch (chunk) {
    case 0: mbar_wait(sbar + B_SEMPTY, sph ^ 1); gu_chunk<0>(pk, s0, s1, sa); break;
    case 1: gu_chunk<1>(pk, s0, s1, sa); break;
    case 2: gu_chunk<2>(pk, s0, s1, sa); break;
    case 3: gu_chunk<3>(pk, s0, s1, sa); break;
    case 4: mbar_wait(sbar + B_SEMPTY + 8, sph ^ 1); gu_chunk<4>(pk, s0, s1, sa); break;
    case 5: gu_chunk<5>(pk, s0, s1, sa); break;
    case 6: gu_chunk<6>(pk, s0, s1, sa); break;
    case 7: gu_chunk<7>(pk, s0, s1, sa); break;
    case 8: mbar_wait(sbar + B_SEMPTY, sph ^ 1); plain_chunk<0>(pk, sa); break;
    case 9: mbar_wait(sbar + B_SEMPTY + 8, sph ^ 1); plain_chunk<1>(pk, sa); break;
    case 10: mbar_wait(sbar + B_SEMPTY, sph ^ 1); plain_chunk<2>(pk, sa); break;
    default: mbar_wait(sbar + B_SEMPTY + 8, sph ^ 1); plain_chunk<3>(pk, sa); break;
  }
}
#define CHUNK_DONE_MASK 0xF88u
#define CHUNK_BUF1_MASK 0xAF0u

__global__ void __launch_bounds__(384, 1) fused_kernel(const __grid_constant__ Params p) {
  extern __shared__ uint8_t smem_raw[];
  const uint32_t sbase = (smem_u32(smem_raw) + 1023) & ~1023u;
  const uint32_t bars = sbase + OFF_BAR;
  const int warp = __shfl_sync(0xffffffff, threadIdx.x >> 5, 0);
  const int lane = threadIdx.x & 31;
  const int b = blockIdx.x;

  if (warp < 4) {
    asm volatile("setmaxnreg.dec.sync.aligned.u32 40;");
    if (warp == 0) {
      if (elect_one()) {
        PROFG(0); PROF(1);
#pragma unroll
        for (int s = 0; s < STAGES; s++) { mbar_init(bars + B_FULL + 8 * s, 1); mbar_init(bars + B_EMPTY + 8 * s, 8); }
#pragma unroll
        for (int s = 0; s < 4; s++) { mbar_init(bars + B_SFULL + 8 * s, 4); mbar_init(bars + B_SEMPTY + 8 * s, 1); }
        mbar_init(bars + B_RECV, 1); mbar_init(bars + B_RECV + 8, 1);
        mbar_init(bars + B_GDONE, 8); mbar_init(bars + B_GREADY, 1); mbar_init(bars + B_EPOCH, 1);
        asm volatile("fence.mbarrier_init.release.cluster;" ::: "memory");
        fence_async_smem();
      }
      __syncwarp();
      asm volatile("bar.arrive 1, 384;" ::: "memory");
      uint32_t seg = first_seg(b);
      uint32_t st = 0, ph = 1, ready = 0, cur_m = 99, ep = 0;
      for (int si = 1; SEG_TYPE(seg) != T_END; si++) {
        const uint32_t type = SEG_TYPE(seg), m = SEG_M(seg), idx = SEG_IDX(seg), k0 = SEG_K0(seg), kend = k0 + SEG_NK(seg),
                       swap = SEG_SWAP(seg);
        if (type >= T_OUTK && m != cur_m) {
          if (cur_m == 99) {
            mbar_wait(bars + B_EPOCH, 0);
            asm volatile("ld.shared.u32 %0, [%1];" : "=r"(ep) : "r"(bars + W_EPOCH) : "memory");
          }
          cur_m = m; ready = 0;
        }
        for (uint32_t kb = k0; kb < kend; kb++) {
          if (type >= T_OUTK) {
            const uint32_t src = kb < 32 ? (kb >> 4) : (kb >> 1) - 14;
            if (!((ready >> src) & 1)) {
              const unsigned target = lane < 2 ? ep * 8 : ep * 2;
              uint32_t it = 0;
              while (true) {
                const unsigned v = ld_acquire(&g_flags[m * 32 + lane]);
                ready = __ballot_sync(0xffffffff, (int)(v - target) >= 0);
                if ((ready >> src) & 1) break;
                __nanosleep(40);
                trap_if(++it > (1u << 22));
              }
              fence_async();
            }
          }
          mbar_wait(bars + B_EMPTY + 8 * st, ph);
          if (elect_one()) {
            const uint32_t fb = bars + B_FULL + 8 * st, sa = sbase + st * ST_BYTES, sb = sa + A_BYTES;
            mbar_expect(fb, type == T_OUTB ? 2 * A_BYTES : ST_BYTES);
            if (type == T_PQ) {
              tma2d(sa, idx < 4 ? &p.sre : &p.sim, kb * 64, m * 128, fb);
              tma3d(sb, &p.xb, kb * 64, (idx & 3) * 4, fb);
            } else if (type == T_GU) {
              tma2d(sa, &p.xa, kb * 64, m * 128, fb);
              tma3d(sb, &p.wg, kb * 64, idx * 2, fb);
              tma3d(sb + 16384, &p.wu, kb * 64, idx * 2, fb);
            } else {
              tma2d(sa, &p.zld, 0, (m * KZ + kb) * 128, fb);
              if (type == T_OUTK) {
                const CUtensorMap* hm = kb < 16 ? &p.hre : &p.him;
                tma2d(sb, hm, (kb & 15) * 64, idx * 256 + swap * 128, fb);
                tma2d(sb + 16384, hm, (kb & 15) * 64, idx * 256 + (swap ^ 1) * 128, fb);
              } else {
                tma3d(sb, &p.wd, (kb - 32) * 64, idx * 4 + swap * 2, fb);
                if (type == T_OUTM) tma3d(sb + 16384, &p.wd, (kb - 32) * 64, idx * 4 + (swap ^ 1) * 2, fb);
              }
            }
          }
          __syncwarp();
          if (++st == STAGES) { st = 0; ph ^= 1; }
        }
        seg = c_sched.s[b][si];
      }
    } else if (warp < 3) {
      asm volatile("bar.sync 1, 384;" ::: "memory");
      if (elect_one()) {
        const uint32_t w = warp - 1;
        const uint32_t stg = sbase + OFF_STG + w * 16384, sbar = bars + w * 16;
        uint32_t ep, fph = 0;
        mbar_wait(bars + B_EPOCH, 0);
        asm volatile("ld.shared.u32 %0, [%1];" : "=r"(ep) : "r"(bars + W_EPOCH) : "memory");
        for (int si = 0;; si++) {
          const uint32_t seg = c_sched.s[b][si];
          const uint32_t epi = SEG_EPI(seg), m = SEG_M(seg), idx = SEG_IDX(seg);
          if (SEG_TYPE(seg) == T_END) break;
          if (epi == E_NONE) continue;
          const uint32_t slot = (m * 4 + idx) * 2 + SEG_SWAP(seg);
          if (epi >= E_FIN) {
            if (epi == E_FINRED) poll_ge(&g_hflag[(m * 4 + idx) * 2 + w], ep);
            poll_ge(&g_xflag[(slot ^ 1) * 2 + w], ep);
            fence_async();
            mbar_expect(bars + B_RECV + 8 * w, 16384);
            tma2d(stg, &p.zld, 0, XROW0 + ((slot ^ 1) * 2 + w) * 128, bars + B_RECV + 8 * w);
            break;
          }
          const uint32_t nsb = (epi == E_PQ || epi == E_HELP) ? 4 : 2;
          uint32_t row, rstep;
          unsigned* flag;
          if (epi == E_PQ) { row = (m * KZ + idx * 4) * 128 + w * 64; rstep = 128; flag = &g_flags[m * 32 + (idx >> 2)]; }
          else if (epi == E_GU) { row = (m * KZ + 32 + idx * 2) * 128 + w * 64; rstep = 128; flag = &g_flags[m * 32 + 2 + idx]; }
          else if (epi == E_SEND) { row = XROW0 + (slot * 2 + w) * 128; rstep = 64; flag = &g_xflag[slot * 2 + w]; }
          else { row = m * 128 + w * 64; rstep = 0; flag = &g_hflag[(m * 4 + idx) * 2 + w]; }
          for (uint32_t sb = 0; sb < nsb; sb++) {
            const uint32_t buf = sb & 1;
            mbar_wait(sbar + B_SFULL + 8 * buf, fph);
            if (epi == E_HELP) {
#pragma unroll
              for (int q = 0; q < 4; q++) tma_store(&p.outm, stg + buf * 8192 + q * 2048, idx * 256 + sb * 64, row + q * 16);
            } else {
              tma_store(&p.zst, stg + buf * 8192, 0, row + sb * rstep);
            }
            bulk_commit();
            bulk_wait_read();
            mbar_arrive(sbar + B_SEMPTY + 8 * buf);
            fph ^= buf;
          }
          bulk_wait();
          red_release(flag);
        }
      }
    } else {
      unsigned ep = 0;
      if (elect_one()) {
        asm volatile("ld.relaxed.gpu.global.u32 %0, [%1];" : "=r"(ep) : "l"(&g_epoch[b]) : "memory");
        prefetch_map(&p.xa); prefetch_map(&p.wg); prefetch_map(&p.wu); prefetch_map(&p.zst); prefetch_map(&p.zld);
        prefetch_map(&p.hre); prefetch_map(&p.him); prefetch_map(&p.wd); prefetch_map(&p.outm);
      }
      __syncwarp();
      asm volatile("bar.sync 1, 384;" ::: "memory");
      if (elect_one()) {
        ep += 1;
        g_epoch[b] = ep;
        asm volatile("st.shared.u32 [%0], %1;" ::"r"(bars + W_EPOCH), "r"(ep) : "memory");
        mbar_arrive(bars + B_EPOCH);
        if (b < 128) {
          mbar_wait(bars + B_GDONE, 0);
          red_release(&g_gatecnt[0]);
        }
        poll_ge(&g_gatecnt[0], ep * 128);
        mbar_arrive(bars + B_GREADY);
      }
    }
  } else {
    asm volatile("setmaxnreg.inc.sync.aligned.u32 232;");
    const uint32_t w = (warp >> 2) - 1, wq = warp & 3;
    if (b < 128) {
      const int row = blk_m(b) * 128 + blk_j(b) * 16 + (warp - 4) * 2;
      const uint4* xr = p.x + row * 128 + lane;
      uint4 xv[8], wv[4];
#pragma unroll
      for (int i = 0; i < 8; i++) xv[i] = __ldg(xr + i * 32);
#pragma unroll
      for (int i = 0; i < 4; i++) wv[i] = __ldg(p.gw + lane + i * 32);
      float z0 = 0.f, z1 = 0.f;
#pragma unroll
      for (int i = 0; i < 4; i++) {
        const uint32_t wa[4] = {wv[i].x, wv[i].y, wv[i].z, wv[i].w};
        const uint32_t a0[4] = {xv[i].x, xv[i].y, xv[i].z, xv[i].w};
        const uint32_t a1[4] = {xv[i + 4].x, xv[i + 4].y, xv[i + 4].z, xv[i + 4].w};
#pragma unroll
        for (int q = 0; q < 4; q++) {
          z0 = fmaf(bf_lo(a0[q]), bf_lo(wa[q]), z0); z0 = fmaf(bf_hi(a0[q]), bf_hi(wa[q]), z0);
          z1 = fmaf(bf_lo(a1[q]), bf_lo(wa[q]), z1); z1 = fmaf(bf_hi(a1[q]), bf_hi(wa[q]), z1);
        }
      }
#pragma unroll
      for (int o = 16; o > 0; o >>= 1) { z0 += __shfl_xor_sync(0xffffffff, z0, o); z1 += __shfl_xor_sync(0xffffffff, z1, o); }
      if (lane < 2) {
        const float z = lane ? z1 : z0;
        const float ic = 1.f + expf(z);
        g_gate[row + lane] = make_float2(1.f / (1.f + expf(-z)), ic > 1e38f ? 1e38f : ic);
      }
      __syncwarp();
    }
    asm volatile("bar.sync 1, 384;" ::: "memory");
    if (b < 128 && lane == 0) mbar_arrive(bars + B_GDONE);

    float d[128];
    uint32_t pk[64];
#pragma unroll
    for (int i = 0; i < 64; i++) pk[i] = 0;
    float s0 = 0.f, s1 = 0.f;
    const uint32_t sbar = bars + w * 16;
    const uint32_t sa_stg = sbase + OFF_STG + w * 16384 + (wq * 16 + (lane & 15)) * 128 + (((lane >> 4) ^ (lane & 7)) << 4);
    const uint32_t da0 = ((sbase + w * 8192) >> 4) | (1u << 16);
    const uint32_t db0 = (sbase + A_BYTES) >> 4;
    const float* gate_ptr = (const float*)g_gate + (w * 64 + wq * 16 + (lane >> 2)) * 2;
    uint32_t st = 0, ph = 0, sph = 0;
    int chunk = 0, chunk_end = 0;
    uint32_t seg = first_seg(b);
    int si = 1;
    bool gate_seen = false;

    while (true) {
      const uint32_t type = SEG_TYPE(seg), epi = SEG_EPI(seg);
      const int nk = SEG_NK(seg);
      uint32_t acc = SEG_FIRST(seg) ^ 1;
      if (threadIdx.x == 128) PROF(7 + si);
      for (int i = 0; i < nk; i++) {
        mbar_wait(bars + B_FULL + 8 * st, ph);
        const uint32_t da = da0 + st * (ST_BYTES >> 4), db = db0 + st * (ST_BYTES >> 4);
        if (type == T_OUTK) {
          wg_fence();
          wgmma256<0>(d, da, db | (1u << 16), acc);
          wgmma256<0>(d, da + 2, (db + 2) | (1u << 16), 1);
          wgmma256<0>(d, da + 4, (db + 4) | (1u << 16), 1);
          wgmma256<0>(d, da + 6, (db + 6) | (1u << 16), 1);
          wg_commit();
        } else {
          wg_fence();
          wgmma256<1>(d, da, db | (512u << 16), acc);
          wgmma256<1>(d, da + 2, (db + 128) | (512u << 16), 1);
          wgmma256<1>(d, da + 4, (db + 256) | (512u << 16), 1);
          wgmma256<1>(d, da + 6, (db + 384) | (512u << 16), 1);
          wg_commit();
        }
        acc = 1;
        const bool pend = chunk < chunk_end;
        if (pend) {
          do_chunk(chunk, pk, s0, s1, sa_stg, sbar, sph);
        } else if (i == 12 && type <= T_GU) {
          if (!gate_seen) { mbar_wait(bars + B_GREADY, 0); gate_seen = true; }
          const float* gp = gate_ptr + SEG_M(seg) * 256 + (type - T_PQ);
          asm volatile("ld.relaxed.gpu.global.f32 %0, [%1];" : "=f"(s0) : "l"(gp) : "memory");
          asm volatile("ld.relaxed.gpu.global.f32 %0, [%1+64];" : "=f"(s1) : "l"(gp) : "memory");
        }
        wg_wait_all(d);
        if (lane == 0) mbar_arrive(bars + B_EMPTY + 8 * st);
        if (pend) {
          if ((CHUNK_DONE_MASK >> chunk) & 1) {
            const uint32_t buf = (CHUNK_BUF1_MASK >> chunk) & 1;
            stage_done(sbar + B_SFULL + 8 * buf);
            sph ^= buf;
          }
          chunk++;
        }
        if (++st == STAGES) { st = 0; ph ^= 1; }
      }
      seg = c_sched.s[b][si++];
      if (epi == E_NONE) continue;
      if (epi == E_PQ) {
        const float sg = SEG_IDX(first_seg(b)) < 4 ? 1.f : -1.f;
        const float m0 = s0 * sg, m1 = s1 * sg;
#pragma unroll
        for (int i = 0; i < 32; i++) { d[4 * i] *= m0; d[4 * i + 1] *= m0; d[4 * i + 2] *= m1; d[4 * i + 3] *= m1; }
      }
#pragma unroll
      for (int i = 32; i < 64; i++) pk[i] = pack2(d[2 * i], d[2 * i + 1]);
      if (epi == E_SEND) break;
#pragma unroll
      for (int i = 0; i < 32; i++) pk[i] = pack2(d[2 * i], d[2 * i + 1]);
      chunk = (epi == E_GU) ? 0 : 8;
      chunk_end = (epi == E_GU) ? 8 : 12;
      if (SEG_TYPE(seg) == T_END) break;
    }

    if (SEG_TYPE(seg) == T_END) {
      for (; chunk < chunk_end; chunk++) {
        do_chunk(chunk, pk, s0, s1, sa_stg, sbar, sph);
        if ((CHUNK_DONE_MASK >> chunk) & 1) {
          const uint32_t buf = (CHUNK_BUF1_MASK >> chunk) & 1;
          stage_done(sbar + B_SFULL + 8 * buf);
          sph ^= buf;
        }
      }
    } else {
      const int nk = SEG_NK(seg);
      if (threadIdx.x == 128) PROF(7 + si);
      for (int i = 0; i < nk; i++) {
        mbar_wait(bars + B_FULL + 8 * st, ph);
        const uint32_t da = da0 + st * (ST_BYTES >> 4), db = (db0 + st * (ST_BYTES >> 4)) | (512u << 16);
        wg_fence();
        wgmma128(d, da, db);
        wgmma128(d, da + 2, db + 128);
        wgmma128(d, da + 4, db + 256);
        wgmma128(d, da + 6, db + 384);
        wg_commit();
        if (i == 0) {
          mbar_wait(sbar + B_SEMPTY, sph ^ 1);
          plain_chunk<2>(pk, sa_stg);
        } else if (i == 1) {
          mbar_wait(sbar + B_SEMPTY + 8, sph ^ 1);
          plain_chunk<3>(pk, sa_stg);
        } else if (i == nk - 1) {
          if (threadIdx.x == 128) PROF(3);
          mbar_wait(bars + B_RECV + 8 * w, 0);
          if (threadIdx.x == 128) PROF(4);
#pragma unroll
          for (int q = 0; q < 8; q++)
            ldsm4((sa_stg + (q >> 2) * 8192) ^ ((q & 3) << 5), pk[4 * q], pk[4 * q + 1], pk[4 * q + 2], pk[4 * q + 3]);
        }
        wg_wait_lo(d);
        if (lane == 0) mbar_arrive(bars + B_EMPTY + 8 * st);
        if (i < 2) stage_done(sbar + B_SFULL + 8 * i);
        if (++st == STAGES) { st = 0; ph ^= 1; }
      }
      if (threadIdx.x == 128) PROF(5);
      const uint32_t col = SEG_IDX(seg) * 256 + SEG_SWAP(seg) * 128, row = SEG_M(seg) * 128 + w * 64 + wq * 16;
      const uint32_t src = sbase + OFF_STG + w * 16384 + wq * 2048;
#pragma unroll
      for (int sb = 0; sb < 2; sb++) {
#pragma unroll
        for (int jj = 0; jj < 4; jj++) {
          uint32_t o[4];
#pragma unroll
          for (int r = 0; r < 4; r++) {
            const int i = 16 * sb + 4 * jj + r;
            o[r] = pack2(d[2 * i] + bf_lo(pk[i]), d[2 * i + 1] + bf_hi(pk[i]));
          }
          stsm4((sa_stg + sb * 8192) ^ (jj << 5), o[0], o[1], o[2], o[3]);
        }
        fence_async();
        __syncwarp();
        if (lane == 0) {
          if (SEG_EPI(seg) == E_FINRED) tma_red(&p.outm, src + sb * 8192, col + sb * 64, row);
          else tma_store(&p.outm, src + sb * 8192, col + sb * 64, row);
          bulk_commit();
        }
      }
      if (lane == 0) bulk_wait_read();
      if (threadIdx.x == 128) { PROF(6); PROFG(2); }
    }
  }
}

typedef CUresult (*EncodeFn)(CUtensorMap*, CUtensorMapDataType, cuuint32_t, void*, const cuuint64_t*, const cuuint64_t*,
                             const cuuint32_t*, const cuuint32_t*, CUtensorMapInterleave, CUtensorMapSwizzle,
                             CUtensorMapL2promotion, CUtensorMapFloatOOBfill);

#define L2PROM CU_TENSOR_MAP_L2_PROMOTION_L2_128B

void map2d(EncodeFn enc, CUtensorMap* m, const void* ptr, uint64_t inner, uint64_t outer, uint32_t rows, bool swz) {
  cuuint64_t dims[2] = {inner, outer}, str[1] = {inner * 2};
  cuuint32_t box[2] = {64, rows}, es[2] = {1, 1};
  enc(m, CU_TENSOR_MAP_DATA_TYPE_BFLOAT16, 2, (void*)ptr, dims, str, box, es, CU_TENSOR_MAP_INTERLEAVE_NONE,
      swz ? CU_TENSOR_MAP_SWIZZLE_128B : CU_TENSOR_MAP_SWIZZLE_NONE, L2PROM, CU_TENSOR_MAP_FLOAT_OOB_FILL_NONE);
}
void map3d(EncodeFn enc, CUtensorMap* m, const void* ptr, uint64_t N, uint64_t K, uint32_t chunks) {
  cuuint64_t dims[3] = {64, K, N / 64}, str[2] = {N * 2, 128};
  cuuint32_t box[3] = {64, 64, chunks}, es[3] = {1, 1, 1};
  enc(m, CU_TENSOR_MAP_DATA_TYPE_BFLOAT16, 3, (void*)ptr, dims, str, box, es, CU_TENSOR_MAP_INTERLEAVE_NONE,
      CU_TENSOR_MAP_SWIZZLE_128B, L2PROM, CU_TENSOR_MAP_FLOAT_OOB_FILL_NONE);
}

}

extern "C" void kernel_launch(void* const* d_in, const int* in_sizes, int n_in, void* d_out, int out_size) {
  (void)in_sizes; (void)n_in; (void)out_size;
  EncodeFn enc = nullptr;
  cudaDriverEntryPointQueryResult q;
  cudaGetDriverEntryPoint("cuTensorMapEncodeTiled", (void**)&enc, cudaEnableDefault, &q);
  void* z = nullptr;
  cudaGetSymbolAddress(&z, g_Z);
  Params p;
  map2d(enc, &p.sre, d_in[1], SEQ, SEQ, 128, true);
  map2d(enc, &p.sim, d_in[2], SEQ, SEQ, 128, true);
  map2d(enc, &p.xa, d_in[0], DM, SEQ, 128, true);
  map3d(enc, &p.xb, d_in[0], DM, SEQ, 4);
  map3d(enc, &p.wg, d_in[6], FF, DM, 2);
  map3d(enc, &p.wu, d_in[7], FF, DM, 2);
  map2d(enc, &p.hre, d_in[3], DM, DM, 128, true);
  map2d(enc, &p.him, d_in[4], DM, DM, 128, true);
  map3d(enc, &p.wd, d_in[8], DM, FF, 2);
  map2d(enc, &p.zld, z, 64, ZROWS, 128, false);
  map2d(enc, &p.zst, z, 64, ZROWS, 64, false);
  map2d(enc, &p.outm, d_out, DM, SEQ, 16, true);
  p.x = (const uint4*)d_in[0];
  p.gw = (const uint4*)d_in[9];
  cudaFuncSetAttribute(fused_kernel, cudaFuncAttributeMaxDynamicSharedMemorySize, SMEM_BYTES);
  fused_kernel<<<NCTA, 384, SMEM_BYTES>>>(p);
}
```

```cpp
#include <cuda_runtime.h>
#include <cuda_bf16.h>
#include <cuda.h>
#include <stdint.h>

#define LEAD 1
#define PRO 1
#define FADDT 0
#define TAIL 0
#define MAPPING 5
#define MAP2 6
#define PREFB 1
#define GWAIT 1
#define SDELAY 0
#define PROMS L2PROM
#define HINTS 0

namespace {

constexpr int SEQ = 2048, DM = 1024, FF = 3584;
constexpr int KZ = 88;
constexpr int ZROWS = 16 * KZ * 128;
constexpr int NBETA = 5;

constexpr int STAGES = 4;
constexpr int A_BYTES = 128 * 64 * 2, B_BYTES = 256 * 64 * 2, ST_BYTES = A_BYTES + B_BYTES;
constexpr int OFF_STG = STAGES * ST_BYTES;
constexpr int OFF_BAR = OFF_STG + 32768;
constexpr int SMEM_BYTES = OFF_BAR + 512 + 1024;
constexpr int B_FULL = 0, B_EMPTY = 32, B_SFULL = 64, B_SEMPTY = 96, B_RECV = 128, B_GLOAD = 144, B_PEER = 176, B_HOK = 184,
              B_GREADY = 192, B_EPOCH = 200, B_TURN = 208, W_EPOCH = 224, W_CLEAR = 228;

enum { T_END = 0, T_PQ = 1, T_GU = 2, T_OUTM = 3, T_OUTK = 4, T_OUTB = 5 };
enum { E_NONE = 0, E_GU = 1, E_PQ = 2, E_HELP = 3, E_SEND = 4, E_FIN = 5, E_FINRED = 6 };

__host__ __device__ constexpr uint32_t mkseg(int type, int m, int idx, int k0, int nk, int first, int swap, int epi) {
  return (uint32_t)type | ((uint32_t)m << 3) | ((uint32_t)idx << 7) | ((uint32_t)k0 << 12) | ((uint32_t)nk << 19) |
         ((uint32_t)first << 26) | ((uint32_t)swap << 27) | ((uint32_t)epi << 28);
}
#define SEG_TYPE(s) ((s) & 7u)
#define SEG_M(s) (((s) >> 3) & 15u)
#define SEG_IDX(s) (((s) >> 7) & 31u)
#define SEG_K0(s) (((s) >> 12) & 127u)
#define SEG_NK(s) (((s) >> 19) & 127u)
#define SEG_FIRST(s) (((s) >> 26) & 1u)
#define SEG_SWAP(s) (((s) >> 27) & 1u)
#define SEG_EPI(s) (((s) >> 28) & 7u)

constexpr int NCTA = 132;
constexpr int MAXSEG = 16;
struct Sched { uint32_t s[132][MAXSEG]; };

__host__ __device__ constexpr int cl_g(int c) { return c < 4 ? 0 : c < 36 ? ((c - 4) & 7) : 1 + (c - 36) - 7 * (((c - 36) * 37) >> 8); }
__host__ __device__ constexpr int cl_r(int c) { return c < 4 ? 4 + c : c < 36 ? ((c - 4) >> 3) : 4 + (((c - 36) * 37) >> 8); }
__host__ __device__ constexpr int map_m(int mp, int b) {
  return (b & 1) + 2 * (mp == 2 ? ((b >> 1) & 7) : mp == 3 ? (b >> 4) : mp == 4 ? cl_r(b >> 1)
       : mp == 5 || mp == 6 ? (cl_g(b >> 1) & 4) + (cl_r(b >> 1) >> 1)
       : mp == 7 || mp == 9 ? (cl_g(b >> 1) & 6) + (cl_r(b >> 1) >> 2) : cl_g(b >> 1));
}
__host__ __device__ constexpr int map_j(int mp, int b) {
  return mp == 2 ? (b >> 4) : mp == 3 ? ((b >> 1) & 7) : mp == 4 ? cl_g(b >> 1)
       : mp == 5 ? 2 * (cl_g(b >> 1) & 3) + (cl_r(b >> 1) & 1)
       : mp == 6 ? (cl_g(b >> 1) & 1) + 2 * (cl_r(b >> 1) & 1) + 2 * (cl_g(b >> 1) & 2)
       : mp == 7 ? 4 * (cl_g(b >> 1) & 1) + (cl_r(b >> 1) & 3)
       : mp == 9 ? (cl_g(b >> 1) & 1) + 2 * (cl_r(b >> 1) & 3) : cl_r(b >> 1);
}
__host__ __device__ constexpr int blk_m(int b) { return map_m(MAPPING, b); }
__host__ __device__ constexpr int blk_j(int b) { return map_j(MAPPING, b); }
__host__ __device__ constexpr uint32_t first_seg(int b) {
  return b < 128 ? mkseg(T_PQ, blk_m(b), blk_j(b), 0, 32, 1, 0, E_PQ)
                 : mkseg(T_GU, (b - 128) * 4, 19, 0, 16, 1, 0, E_GU);
}

constexpr Sched make_sched() {
  Sched t{};
  const int r3[4] = {19, 20, 26, 27};
  for (int b = 0; b < 128; b++) {
    int m = blk_m(b), j = blk_j(b), c = 0;
    t.s[b][c++] = first_seg(b);
    t.s[b][c++] = mkseg(T_GU, m, j < 3 ? j : 18 + j, 0, 16, 1, 0, E_GU);
    t.s[b][c++] = mkseg(T_GU, m, 3 + j, 0, 16, 1, 0, E_GU);
    t.s[b][c++] = mkseg(T_GU, m, 11 + j, 0, 16, 1, 0, E_GU);
    m = map_m(MAP2, b); j = map_j(MAP2, b);
    const int n = j >> 1, r = b & 1;
    m = (m & ~1) | (j & 1);
    if (!r) {
      t.s[b][c++] = mkseg(T_OUTM, m, n, 32, 14, 1, 0, E_NONE);
      t.s[b][c++] = mkseg(T_OUTK, m, n, 0, 16, 0, 0, E_NONE);
      t.s[b][c++] = mkseg(T_OUTK, m, n, 16, 16, 0, 0, E_SEND);
    } else if (n == 0) {
      t.s[b][c++] = mkseg(T_OUTM, m, 1, 74, 9, 1, 0, E_HELP);
      t.s[b][c++] = mkseg(T_OUTM, m, 0, 76, 7, 1, 1, E_NONE);
      t.s[b][c++] = mkseg(T_OUTM, m, 0, 46, 30, 0, 1, E_SEND);
    } else {
      t.s[b][c++] = mkseg(T_GU, m, r3[n], 0, 16, 1, 0, E_GU);
      t.s[b][c++] = mkseg(T_OUTM, m, n, 46, n == 1 || (n == 2 && (m & 3) == 0) ? 28 : 30, 1, 1, E_SEND);
    }
    t.s[b][c++] = mkseg(T_OUTB, m, n, KZ - NBETA, NBETA, 0, r, n == 0 ? E_FIN : E_FINRED);
  }
  for (int e = 0; e < 4; e++) {
    int c = 0;
    for (int q = 0; q < 4; q++) t.s[128 + e][c++] = mkseg(T_GU, 4 * e + q, r3[0], 0, 16, 1, 0, E_GU);
    for (int q = 0; q < 8; q++) t.s[128 + e][c++] = mkseg(T_OUTM, 4 * e + (q & 3), 2 + (q >> 2), q ? 76 : 74, q ? 7 : 9, 1, 0, E_HELP);
  }
  return t;
}
__constant__ Sched c_sched = make_sched();

struct Sync {
  float2 gate[SEQ];
  unsigned flags[16 * 32];
  unsigned hflag[128];
  unsigned epoch[160];
  unsigned gatecnt[32];
};
struct Params {
  const uint4* x;
  const uint4* gw;
  Sync* sync;
  uint4* out;
  long long* prof;
  uint32_t first[132];
  CUtensorMap sre, sim, xa, xb, wg, wu, hre, him, wd, zld, zst, outm;
};

__device__ __align__(1024) __nv_bfloat16 g_Z[(size_t)ZROWS * 64];
__device__ __align__(128) Sync g_sync;
#define PROF(slot)
#define PROFIF(cond, slot)
#define PROFG(slot)
#define PROFDUMP()
#define PROFINIT()
#define PSET 0

__device__ __forceinline__ uint32_t smem_u32(const void* p) { return (uint32_t)__cvta_generic_to_shared(p); }
__device__ __forceinline__ void mbar_init(uint32_t a, uint32_t c) {
  asm volatile("mbarrier.init.shared::cta.b64 [%0], %1;" ::"r"(a), "r"(c) : "memory");
}
__device__ __forceinline__ void mbar_expect(uint32_t a, uint32_t bytes) {
  asm volatile("mbarrier.arrive.expect_tx.shared::cta.b64 _, [%0], %1;" ::"r"(a), "r"(bytes) : "memory");
}
__device__ __forceinline__ void mbar_arrive(uint32_t a) {
  asm volatile("mbarrier.arrive.shared::cta.b64 _, [%0];" ::"r"(a) : "memory");
}
__device__ __forceinline__ void mbar_wait(uint32_t a, uint32_t parity) {
  asm volatile(
      "{ .reg .pred p; .reg .u32 it;\n"
      "mov.u32 it, 0;\n"
      "WAIT_LOOP:\n"
      "mbarrier.try_wait.parity.shared::cta.b64 p, [%0], %1;\n"
      "@p bra WAIT_DONE;\n"
      "add.u32 it, it, 1;\n"
      "setp.lt.u32 p, it, 0x100000;\n"
      "@p bra WAIT_LOOP;\n"
      "trap;\n"
      "WAIT_DONE:\n"
      "}" ::"r"(a), "r"(parity) : "memory");
}
__device__ __forceinline__ bool mbar_test(uint32_t a, uint32_t parity) {
  uint32_t ok;
  asm volatile("{ .reg .pred p; mbarrier.test_wait.parity.shared::cta.b64 p, [%1], %2; selp.u32 %0, 1, 0, p; }"
               : "=r"(ok) : "r"(a), "r"(parity) : "memory");
  return ok;
}
__device__ __forceinline__ void trap_if(bool c) {
  asm volatile("{ .reg .pred p; setp.ne.u32 p, %0, 0; @p trap; }" ::"r"((uint32_t)c));
}
template <typename T>
__device__ __forceinline__ T* ptr_add(T* base, uint32_t bytes) {
  uint64_t r;
  asm("{ .reg .u32 lo, hi; mov.b64 {lo, hi}, %1; add.cc.u32 lo, lo, %2; addc.u32 hi, hi, 0; mov.b64 %0, {lo, hi}; }"
      : "=l"(r) : "l"(base), "r"(bytes));
  return (T*)r;
}
__device__ __forceinline__ unsigned ld_acquire(const unsigned* p) {
  unsigned v;
  asm volatile("ld.acquire.gpu.global.u32 %0, [%1];" : "=r"(v) : "l"(p) : "memory");
  return v;
}
__device__ __forceinline__ void red_release(unsigned* p) {
  asm volatile("red.release.gpu.global.add.u32 [%0], 1;" ::"l"(p) : "memory");
}
__device__ __forceinline__ void poll_ge(const unsigned* p, unsigned target) {
  uint32_t it = 0;
  while ((int)(ld_acquire(p) - target) < 0) {
    __nanosleep(40);
    trap_if(++it > (1u << 22));
  }
}
__device__ __forceinline__ void fence_async() { asm volatile("fence.proxy.async.global;" ::: "memory"); }
__device__ __forceinline__ void fence_async_smem() { asm volatile("fence.proxy.async.shared::cta;" ::: "memory"); }
constexpr uint64_t POL_NORMAL = 0x1000000000000000ull, POL_FIRST = 0x12F0000000000000ull;
__device__ __forceinline__ void tma2d(uint32_t dst, const CUtensorMap* m, int c0, int c1, uint32_t bar, uint64_t pol) {
  asm volatile("cp.async.bulk.tensor.2d.shared::cluster.global.mbarrier::complete_tx::bytes.L2::cache_hint [%0], [%1, {%3, %4}], [%2], %5;"
               ::"r"(dst), "l"(m), "r"(bar), "r"(c0), "r"(c1), "l"(pol) : "memory");
}
__device__ __forceinline__ void tma3d(uint32_t dst, const CUtensorMap* m, int c0, int c1, int c2, uint32_t bar, uint64_t pol) {
  asm volatile("cp.async.bulk.tensor.3d.shared::cluster.global.mbarrier::complete_tx::bytes.L2::cache_hint [%0], [%1, {%3, %4, %5}], [%2], %6;"
               ::"r"(dst), "l"(m), "r"(bar), "r"(c0), "r"(c1), "r"(c2), "l"(pol) : "memory");
}
__device__ __forceinline__ void tma_store(const CUtensorMap* m, uint32_t src, int c0, int c1) {
  asm volatile("cp.async.bulk.tensor.2d.global.shared::cta.bulk_group [%0, {%2, %3}], [%1];"
               ::"l"(m), "r"(src), "r"(c0), "r"(c1) : "memory");
}
__device__ __forceinline__ void tma_red(const CUtensorMap* m, uint32_t src, int c0, int c1) {
  asm volatile("cp.reduce.async.bulk.tensor.2d.global.shared::cta.add.bulk_group [%0, {%2, %3}], [%1];"
               ::"l"(m), "r"(src), "r"(c0), "r"(c1) : "memory");
}
__device__ __forceinline__ uint32_t map_peer(uint32_t a, uint32_t cta) {
  uint32_t r;
  asm("mapa.shared::cluster.u32 %0, %1, %2;" : "=r"(r) : "r"(a), "r"(cta));
  return r;
}
__device__ __forceinline__ void mbar_arrive_remote(uint32_t a) {
  asm volatile("mbarrier.arrive.shared::cluster.b64 _, [%0];" ::"r"(a) : "memory");
}
__device__ __forceinline__ void bulk_commit() { asm volatile("cp.async.bulk.commit_group;" ::: "memory"); }
__device__ __forceinline__ void bulk_wait_read() { asm volatile("cp.async.bulk.wait_group.read 0;" ::: "memory"); }
__device__ __forceinline__ void bulk_wait() { asm volatile("cp.async.bulk.wait_group 0;" ::: "memory"); }
__device__ __forceinline__ void prefetch_map(const CUtensorMap* m) {
  asm volatile("prefetch.tensormap [%0];" ::"l"(m) : "memory");
}
__device__ __forceinline__ bool elect_one() {
  uint32_t p;
  asm volatile("{ .reg .pred p; elect.sync _|p, 0xffffffff; selp.u32 %0, 1, 0, p; }" : "=r"(p));
  return p;
}
__device__ __forceinline__ void stsm4(uint32_t a, uint32_t r0, uint32_t r1, uint32_t r2, uint32_t r3) {
  asm volatile("stmatrix.sync.aligned.m8n8.x4.shared.b16 [%0], {%1,%2,%3,%4};" ::"r"(a), "r"(r0), "r"(r1), "r"(r2), "r"(r3) : "memory");
}
__device__ __forceinline__ uint32_t pack2(float lo, float hi) {
  uint32_t r;
  asm("cvt.rn.bf16x2.f32 %0, %1, %2;" : "=r"(r) : "f"(hi), "f"(lo));
  return r;
}
__device__ __forceinline__ float bf_lo(uint32_t v) { return __uint_as_float(v << 16); }
__device__ __forceinline__ float bf_hi(uint32_t v) { return __uint_as_float(v & 0xffff0000u); }
__device__ __forceinline__ float ex2f(float x) { float r; asm("ex2.approx.ftz.f32 %0, %1;" : "=f"(r) : "f"(x)); return r; }
__device__ __forceinline__ float rcpf(float x) { float r; asm("rcp.approx.ftz.f32 %0, %1;" : "=f"(r) : "f"(x)); return r; }

#define R8(d, i) "+f"(d[i]), "+f"(d[i + 1]), "+f"(d[i + 2]), "+f"(d[i + 3]), "+f"(d[i + 4]), "+f"(d[i + 5]), "+f"(d[i + 6]), "+f"(d[i + 7])
#define R64LO(d) R8(d, 0), R8(d, 8), R8(d, 16), R8(d, 24), R8(d, 32), R8(d, 40), R8(d, 48), R8(d, 56)
#define R64HI(d) R8(d, 64), R8(d, 72), R8(d, 80), R8(d, 88), R8(d, 96), R8(d, 104), R8(d, 112), R8(d, 120)
#define S64LO "%0,%1,%2,%3,%4,%5,%6,%7,%8,%9,%10,%11,%12,%13,%14,%15,%16,%17,%18,%19,%20,%21,%22,%23,%24,%25,%26,%27,%28,%29,%30,%31," \
              "%32,%33,%34,%35,%36,%37,%38,%39,%40,%41,%42,%43,%44,%45,%46,%47,%48,%49,%50,%51,%52,%53,%54,%55,%56,%57,%58,%59,%60,%61,%62,%63"
#define S64HI "%64,%65,%66,%67,%68,%69,%70,%71,%72,%73,%74,%75,%76,%77,%78,%79,%80,%81,%82,%83,%84,%85,%86,%87,%88,%89,%90,%91,%92,%93,%94,%95," \
              "%96,%97,%98,%99,%100,%101,%102,%103,%104,%105,%106,%107,%108,%109,%110,%111,%112,%113,%114,%115,%116,%117,%118,%119,%120,%121,%122,%123,%124,%125,%126,%127"

constexpr uint32_t DESC_HI = 0x40000040u;
__device__ __forceinline__ uint64_t mkdesc(uint32_t lo) { return ((uint64_t)DESC_HI << 32) | lo; }

template <int TB>
__device__ __forceinline__ void wgmma256(float (&d)[128], uint32_t da, uint32_t db, uint32_t acc) {
  asm volatile("{ .reg .pred p; setp.ne.b32 p, %130, 0;\n"
               "wgmma.mma_async.sync.aligned.m64n256k16.f32.bf16.bf16 {" S64LO "," S64HI "}, %128, %129, p, 1, 1, 0, %131; }"
               : R64LO(d), R64HI(d) : "l"(mkdesc(da)), "l"(mkdesc(db)), "r"(acc), "n"(TB));
}
__device__ __forceinline__ void wgmma128(float (&d)[128], uint32_t da, uint32_t db) {
  asm volatile("wgmma.mma_async.sync.aligned.m64n128k16.f32.bf16.bf16 {" S64LO "}, %64, %65, 1, 1, 1, 0, 1;"
               : R64LO(d) : "l"(mkdesc(da)), "l"(mkdesc(db)));
}
__device__ __forceinline__ void wg_fence() { asm volatile("wgmma.fence.sync.aligned;" ::: "memory"); }
__device__ __forceinline__ void wg_commit() { asm volatile("wgmma.commit_group.sync.aligned;" ::: "memory"); }
__device__ __forceinline__ void wg_wait_all(float (&d)[128]) {
  asm volatile("wgmma.wait_group.sync.aligned 0;" : R64LO(d), R64HI(d)::"memory");
}
__device__ __forceinline__ void wg_wait_lo(float (&d)[128]) {
  asm volatile("wgmma.wait_group.sync.aligned 0;" : R64LO(d)::"memory");
}

__device__ __forceinline__ void stage_done(uint32_t bar) {
  fence_async_smem();
  __syncwarp();
  if (elect_one()) mbar_arrive(bar);
}

template <int C>
__device__ __forceinline__ void gu_chunk(uint32_t (&pk)[64], float ic0, float ic1, uint32_t sa) {
  uint32_t o[4];
#pragma unroll
  for (int r = 0; r < 4; r++) {
    asm volatile("" : "+r"(pk[4 * C + r]), "+r"(pk[32 + 4 * C + r]));
    const uint32_t G = pk[4 * C + r], U = pk[32 + 4 * C + r];
    const float ic = (r & 1) ? ic1 : ic0;
    const float e0 = ex2f(bf_lo(G) * -1.4426950408889634f), e1 = ex2f(bf_hi(G) * -1.4426950408889634f);
    o[r] = pack2(bf_lo(U) * rcpf(fmaf(e0, ic, ic)), bf_hi(U) * rcpf(fmaf(e1, ic, ic)));
  }
  stsm4((sa + (C >> 2) * 8192) ^ ((C & 3) << 5), o[0], o[1], o[2], o[3]);
}
template <int C>
__device__ __forceinline__ void plain_chunk(uint32_t (&pk)[64], float m0, float m1, uint32_t sa) {
#pragma unroll
  for (int jj = 0; jj < 4; jj++) {
    uint32_t o[4];
#pragma unroll
    for (int r = 0; r < 4; r++) {
      asm volatile("" : "+r"(pk[16 * C + 4 * jj + r]));
      const uint32_t v = pk[16 * C + 4 * jj + r];
      const float m = (r & 1) ? m1 : m0;
      o[r] = pack2(bf_lo(v) * m, bf_hi(v) * m);
    }
    stsm4((sa + (C & 1) * 8192) ^ (jj << 5), o[0], o[1], o[2], o[3]);
  }
}

struct Loads {
  const CUtensorMap *ma, *mb0, *mb1;
  int a0, a1, da0, da1, b0, b1, db0, db1, c0, c1, e1;
  uint64_t pa, pb;
};
__device__ __forceinline__ Loads seg_loads(const Params& p, uint32_t seg) {
  const int type = SEG_TYPE(seg), m = SEG_M(seg), idx = SEG_IDX(seg), k0 = SEG_K0(seg), swap = SEG_SWAP(seg);
  Loads l;
  l.pa = ((HINTS & 1) && type == T_PQ) || ((HINTS & 8) && type > T_GU) ? POL_FIRST : POL_NORMAL;
  l.pb = ((HINTS & 2) && type == T_GU) || ((HINTS & 4) && type > T_GU) ? POL_FIRST : POL_NORMAL;
  if (type <= T_GU) {
    l.a0 = k0 * 64; l.a1 = m * 128; l.da0 = 64; l.da1 = 0;
    l.b0 = 0; l.b1 = k0 * 64; l.db0 = 0; l.db1 = 64; l.e1 = 0;
    if (type == T_PQ) { l.ma = idx < 4 ? &p.sre : &p.sim; l.mb0 = l.mb1 = &p.xb; l.c0 = (idx & 3) * 4; l.c1 = l.c0 + 2; }
    else { l.ma = &p.xa; l.mb0 = &p.wg; l.mb1 = &p.wu; l.c0 = l.c1 = idx * 2; }
  } else {
    l.ma = &p.zld; l.a0 = 0; l.a1 = (m * KZ + k0) * 128; l.da0 = 0; l.da1 = 128;
    if (type == T_OUTK) {
      l.mb0 = l.mb1 = k0 < 16 ? &p.hre : &p.him;
      l.b0 = (k0 & 15) * 64; l.b1 = idx * 256 + swap * 128; l.db0 = 64; l.db1 = 0; l.c0 = l.c1 = 0; l.e1 = 128 - swap * 256;
    } else {
      l.mb0 = l.mb1 = &p.wd;
      l.b0 = 0; l.b1 = (k0 - 32) * 64; l.db0 = 0; l.db1 = 64; l.c0 = idx * 4 + swap * 2; l.c1 = l.c0 ^ 2; l.e1 = 0;
    }
  }
  return l;
}
__device__ __forceinline__ void issue_loads(Loads& l, uint32_t sa, uint32_t fb) {
  mbar_expect(fb, ST_BYTES);
  tma2d(sa, l.ma, l.a0, l.a1, fb, l.pa);
  tma3d(sa + A_BYTES, l.mb0, l.b0, l.b1, l.c0, fb, l.pb);
  tma3d(sa + A_BYTES + 16384, l.mb1, l.b0, l.b1 + l.e1, l.c1, fb, l.pb);
  l.a0 += l.da0; l.a1 += l.da1; l.b0 += l.db0; l.b1 += l.db1;
}

template <int KM>
__device__ __forceinline__ void mma_block(float (&d)[128], uint32_t da, uint32_t db, uint32_t acc) {
  constexpr uint32_t LBO = KM ? (1u << 16) : (512u << 16), STEP = KM ? 2 : 128;
  wg_fence();
  wgmma256<1 - KM>(d, da, db + LBO, acc);
  wgmma256<1 - KM>(d, da + 2, db + (LBO + STEP), 1);
  wgmma256<1 - KM>(d, da + 4, db + (LBO + 2 * STEP), 1);
  wgmma256<1 - KM>(d, da + 6, db + (LBO + 3 * STEP), 1);
  wg_commit();
}

#define ADVANCE()                                          \
  const uint32_t ebar = fbar + (B_EMPTY - B_FULL);         \
  asm volatile("" : "+r"(st));                             \
  st = (st + 1) & (STAGES - 1);                            \
  ph ^= (st == 0);                                         \
  fbar = bars + B_FULL + 8 * st;                           \
  da = da0 + st * (ST_BYTES >> 4);                         \
  db = db0 + st * (ST_BYTES >> 4);                         \
  full = mbar_test(fbar, ph);
#define KSTEP(KM, WORK)                                    \
  {                                                        \
    if (!full) mbar_wait(fbar, ph);                        \
    mma_block<KM>(d, da, db, acc);                         \
    acc = 1;                                               \
    WORK;                                                  \
    ADVANCE();                                             \
    wg_wait_all(d);                                        \
    if (lane == 0) mbar_arrive(ebar);                      \
  }
#define SWAIT(buf) mbar_wait(sbar + B_SEMPTY + 8 * (buf), sph ^ 1)
#define SDONE(buf) stage_done(sbar + B_SFULL + 8 * (buf))

__global__ void __cluster_dims__(2, 1, 1) __launch_bounds__(384, 1) fused_kernel(const __grid_constant__ Params p) {
  extern __shared__ uint8_t smem_raw[];
  const uint32_t sbase = (smem_u32(smem_raw) + 1023) & ~1023u;
  const uint32_t bars = sbase + OFF_BAR;
  const int warp = __shfl_sync(0xffffffff, threadIdx.x >> 5, 0);
  const int lane = threadIdx.x & 31;
  const int b = blockIdx.x;
  const uint32_t seg0 = p.first[b];

  if (PSET == 1) PROFIF(threadIdx.x == 128, 44);

  if (warp >= 4) {
    asm volatile("setmaxnreg.inc.sync.aligned.u32 224;");
    if (PSET == 1) PROFIF(threadIdx.x == 128, 46);
    const uint32_t w = (warp >> 2) - 1, wq = warp & 3;
    float d[128];
    uint32_t pk[64];
    float s0 = 0.f, s1 = 0.f;
    const uint32_t sbar = bars + w * 16;
    const uint32_t lane_off = (wq * 16 + (lane & 15)) * 128 + (((lane >> 4) ^ (lane & 7)) << 4);
    const uint32_t sa_stg = sbase + OFF_STG + w * 16384 + lane_off;
    const uint32_t da0 = (((sbase + w * 8192) & 0x3FFFF) >> 4) | (1u << 16);
    const uint32_t db0 = ((sbase + A_BYTES) & 0x3FFFF) >> 4;
    uint32_t st = 0, ph = 0, sph = 0, fbar = bars + B_FULL, da = da0, db = db0, acc = 0;
    uint32_t seg = seg0, next = 0;
    int si = 1, left = SEG_NK(seg);
    bool full = false;
    asm volatile("bar.sync 1, 384;" ::: "memory");
    asm volatile("barrier.cluster.arrive.relaxed.aligned;" ::: "memory");
    if (PSET == 1) PROFIF(threadIdx.x == 128, 47);

    if (w == 1) {
      mbar_wait(fbar, 0);
      const uint32_t t0 = (uint32_t)clock();
      while ((uint32_t)clock() - t0 < 200u);
    }
    while (true) {
      const int epi = SEG_EPI(seg);
      if (SEG_TYPE(seg) < T_OUTK) {
        for (; left > (epi != E_NONE && epi != E_SEND); left--)
          KSTEP(0,
            if (left <= 4) {
              next = c_sched.s[b][si];
              if (left == 2 && SEG_TYPE(seg) <= T_GU) {
                if (si == 1) { mbar_wait(bars + B_GREADY, 0); asm volatile("barrier.cluster.wait.aligned;" ::: "memory"); }
                const float2* gp = ptr_add(p.sync->gate, (SEG_M(seg) * 128 + w * 64 + wq * 16 + (lane >> 2)) * 8 + (SEG_TYPE(seg) - T_PQ) * 4);
                asm volatile("ld.relaxed.gpu.global.f32 %0, [%1];" : "=f"(s0) : "l"(gp) : "memory");
                asm volatile("ld.relaxed.gpu.global.f32 %0, [%1+64];" : "=f"(s1) : "l"(gp) : "memory");
              }
            })
      } else {
        for (; left > 0; left--) KSTEP(1, next = c_sched.s[b][si])
      }
      const bool neg = SEG_IDX(seg) >= 4;
      const uint32_t lcol = SEG_IDX(seg) * 256, lrow = SEG_M(seg) * 128;
      seg = next;
      si++;
      left = SEG_NK(seg);
      if (epi > E_GU) {
        if (epi == E_SEND) break;
        KSTEP(0, if (epi != E_PQ) s0 = s1 = 1.f; else if (neg) { s0 = -s0; s1 = -s1; })
#pragma unroll
        for (int i = 0; i < 64; i++) pk[i] = pack2(d[2 * i], d[2 * i + 1]);
        acc = 0;
        if (SEG_TYPE(seg) == T_END) {
          const uint32_t q = st + w, fs = sbase + (q & 3) * ST_BYTES;
          mbar_wait(bars + B_EMPTY + 8 * (q & 3), ph ^ (q >> 2) ^ 1);
#pragma unroll
          for (int sb = 0; sb < 4; sb++) {
#pragma unroll
            for (int jj = 0; jj < 4; jj++)
              stsm4((fs + lane_off + sb * 8192) ^ (jj << 5), pk[16 * sb + 4 * jj], pk[16 * sb + 4 * jj + 1],
                    pk[16 * sb + 4 * jj + 2], pk[16 * sb + 4 * jj + 3]);
            fence_async_smem();
            __syncwarp();
            if (lane == 0) tma_store(&p.outm, fs + wq * 2048 + sb * 8192, lcol + sb * 64, lrow + w * 64 + wq * 16);
          }
          if (lane == 0) { bulk_commit(); bulk_wait(); mbar_arrive(sbar + B_SFULL); }
          break;
        }
        KSTEP(0, SWAIT(0); plain_chunk<0>(pk, s0, s1, sa_stg); SDONE(0))
        KSTEP(0, SWAIT(1); plain_chunk<1>(pk, s0, s1, sa_stg); SDONE(1); sph ^= 1)
        KSTEP(0, next = c_sched.s[b][si])
        KSTEP(0, SWAIT(0); plain_chunk<2>(pk, s0, s1, sa_stg); SDONE(0))
        KSTEP(0, SWAIT(1); plain_chunk<3>(pk, s0, s1, sa_stg); SDONE(1); sph ^= 1)
        left -= 5;
      } else {
        if (epi == E_NONE) continue;
        KSTEP(0, )
#pragma unroll
        for (int i = 0; i < 64; i++) pk[i] = pack2(d[2 * i], d[2 * i + 1]);
        acc = 0;
        KSTEP(0, SWAIT(0); gu_chunk<0>(pk, s0, s1, sa_stg))
        KSTEP(0, gu_chunk<1>(pk, s0, s1, sa_stg))
        KSTEP(0, gu_chunk<2>(pk, s0, s1, sa_stg))
        KSTEP(0, gu_chunk<3>(pk, s0, s1, sa_stg); SDONE(0))
        KSTEP(0, SWAIT(1); gu_chunk<4>(pk, s0, s1, sa_stg))
        KSTEP(0, gu_chunk<5>(pk, s0, s1, sa_stg))
        KSTEP(0, gu_chunk<6>(pk, s0, s1, sa_stg); next = c_sched.s[b][si])
        KSTEP(0, gu_chunk<7>(pk, s0, s1, sa_stg); SDONE(1); sph ^= 1)
        left -= 8;
      }
    }

    if (SEG_TYPE(seg) != T_END) {
#define BETA_BLOCK(QA, RA, QB, RB)                                                                     \
  {                                                                                                    \
    const uint32_t a = da0 + ((st + QA) & 3) * (ST_BYTES >> 4) + RA * 1024;                            \
    const uint32_t bb = db0 + ((st + QB) & 3) * (ST_BYTES >> 4) + ((512u << 16) + RB * 1024 - 1024);   \
    wgmma128(d, a, bb); wgmma128(d, a + 2, bb + 128); wgmma128(d, a + 4, bb + 256); wgmma128(d, a + 6, bb + 384); \
  }
#define BETA_FULL(Q) mbar_wait(bars + B_FULL + 8 * ((st + Q) & 3), ph ^ ((st + Q) >> 2))
      const uint32_t xoff = OFF_STG + w * 16384 + wq * 2048 + lane * 16;
      if (PSET == 3) PROFIF((threadIdx.x & 127) == 0, 24 + 16 * w);
      if (!full) mbar_wait(fbar, ph);
      wg_fence();
      BETA_BLOCK(0, 0, 0, 1)
      BETA_FULL(1);
      wg_fence();
      BETA_BLOCK(0, 2, 1, 0)
      wg_commit();
      if (PSET == 3) PROFIF((threadIdx.x & 127) == 0, 25 + 16 * w);
      BETA_FULL(2);
      {
        const uint32_t dst = map_peer(sbase + xoff, (b & 1) ^ 1), dbar = map_peer(bars + B_RECV + 8 * w, (b & 1) ^ 1);
        mbar_wait(bars + B_PEER, 0);
#pragma unroll
        for (int q = 0; q < 8; q++) {
          const int i = 64 + 8 * q;
          asm volatile("st.async.weak.shared::cluster.mbarrier::complete_tx::bytes.v4.b32 [%0], {%1,%2,%3,%4}, [%5];"
                       ::"r"(dst + (q >> 2) * 8192 + (q & 3) * 512), "r"(pack2(d[i], d[i + 1])), "r"(pack2(d[i + 2], d[i + 3])),
                         "r"(pack2(d[i + 4], d[i + 5])), "r"(pack2(d[i + 6], d[i + 7])), "r"(dbar) : "memory");
        }
      }
      if (PSET == 3) PROFIF((threadIdx.x & 127) == 0, 26 + 16 * w);
      wg_wait_lo(d);
      if (PSET == 3) PROFIF((threadIdx.x & 127) == 0, 27 + 16 * w);
      wg_fence();
      BETA_BLOCK(1, 1, 1, 2)
      BETA_BLOCK(2, 0, 2, 1)
      if (PSET == 3) PROFIF((threadIdx.x & 127) == 0, 28 + 16 * w);
      BETA_FULL(3);
      if (PSET == 3) PROFIF((threadIdx.x & 127) == 0, 29 + 16 * w);
      wg_fence();
      BETA_BLOCK(2, 2, 3, 0)
      wg_commit();
      PROFIF(threadIdx.x == 128, 3);
      if (PSET == 3) PROFIF((threadIdx.x & 127) == 0, 32 + 16 * w);
      mbar_wait(bars + B_RECV + 8 * w, 0);
      PROFIF(threadIdx.x == 128, 4);
#pragma unroll
      for (int q = 0; q < 8; q++)
        asm volatile("ld.shared.v4.u32 {%0,%1,%2,%3}, [%4];" : "=r"(pk[4 * q]), "=r"(pk[4 * q + 1]), "=r"(pk[4 * q + 2]), "=r"(pk[4 * q + 3])
                     : "r"(sbase + xoff + (q >> 2) * 8192 + (q & 3) * 512) : "memory");
      __syncwarp();
      const uint32_t rcv = sbase + OFF_STG + w * 16384;
      const uint32_t col = SEG_IDX(seg) * 256 + SEG_SWAP(seg) * 128, row = SEG_M(seg) * 128 + w * 64 + wq * 16;
      mbar_wait(bars + B_HOK, 0);
      if (PSET == 3) PROFIF((threadIdx.x & 127) == 0, 33 + 16 * w);
      wg_wait_lo(d);
      PROFIF(threadIdx.x == 128, 5);
      if (PSET == 3) PROFIF((threadIdx.x & 127) == 0, 34 + 16 * w);
      const bool addto = SEG_EPI(seg) == E_FINRED;
#pragma unroll
      for (int sb = 0; sb < 2; sb++) {
#pragma unroll
        for (int jj = 0; jj < 4; jj++) {
          uint32_t o[4];
#pragma unroll
          for (int r = 0; r < 4; r++) {
            const int i = 32 * sb + 8 * jj + 2 * r;
            asm("add.rn.bf16x2 %0, %1, %2;" : "=r"(o[r]) : "r"(pack2(d[i], d[i + 1])), "r"(pk[i >> 1]));
          }
          stsm4((sa_stg + sb * 8192) ^ (jj << 5), o[0], o[1], o[2], o[3]);
        }
        fence_async_smem();
        __syncwarp();
        if (elect_one()) {
          if (addto) tma_red(&p.outm, rcv + wq * 2048 + sb * 8192, col + sb * 64, row);
          else tma_store(&p.outm, rcv + wq * 2048 + sb * 8192, col + sb * 64, row);
        }
      }
      if (PSET == 3) PROFIF((threadIdx.x & 127) == 0, 35 + 16 * w);
      if (elect_one()) { bulk_commit(); bulk_wait_read(); }
      if (PSET == 3) PROFIF((threadIdx.x & 127) == 0, 36 + 16 * w);
    }
  } else {
    asm volatile("setmaxnreg.dec.sync.aligned.u32 56;");
    if (warp > 2) {
      unsigned ep = 0;
      asm volatile("bar.sync 1, 384;" ::: "memory");
      asm volatile("barrier.cluster.arrive.relaxed.aligned;" ::: "memory");
      if (lane == 0) {
        PROFG(0);
        asm volatile("ld.relaxed.gpu.global.u32 %0, [%1];" : "=r"(ep) : "l"(&p.sync->epoch[b]) : "memory");
        ep += 1;
        p.sync->epoch[b] = ep;
        asm volatile("st.shared.u32 [%0], %1;" ::"r"(bars + W_EPOCH), "r"(ep) : "memory");
        mbar_arrive(bars + B_EPOCH);
        prefetch_map(&p.xa); prefetch_map(&p.wg); prefetch_map(&p.wu); prefetch_map(&p.zst); prefetch_map(&p.zld);
        prefetch_map(&p.hre); prefetch_map(&p.him); prefetch_map(&p.wd); prefetch_map(&p.outm);
        __nanosleep(3000);
        poll_ge(&p.sync->gatecnt[0], ep * 256);
        mbar_arrive(bars + B_GREADY);
      }
      ep = __shfl_sync(0xffffffff, ep, 0);
      const unsigned target = lane < 2 ? ep * 4 : ep;
      uint32_t ready = 0, cur_m = 99, cnt = 0, published = 0;
      for (int si = 1;; si++) {
        const uint32_t seg = c_sched.s[b][si];
        const uint32_t type = SEG_TYPE(seg), m = SEG_M(seg);
        if (type == T_END) break;
        if (type < T_OUTM) continue;
        if (m != cur_m) { cur_m = m; ready = 0; }
        const unsigned* fp = ptr_add(p.sync->flags, (m * 32 + lane) * 4);
        const uint32_t kend = SEG_K0(seg) + SEG_NK(seg);
        for (uint32_t kb = SEG_K0(seg); kb < kend; kb++) {
          const uint32_t src = kb < 32 ? (kb >> 4) : (kb >> 1) - 14;
          if (!((ready >> src) & 1)) {
            if (cnt != published) {
              published = cnt;
              if (lane == 0) asm volatile("st.release.cta.shared.u32 [%0], %1;" ::"r"(bars + W_CLEAR), "r"(cnt) : "memory");
            }
            uint32_t it = 0;
            while (true) {
              const unsigned v = ld_acquire(fp);
              ready = __ballot_sync(0xffffffff, (int)(v - target) >= 0);
              if ((ready >> src) & 1) break;
              __nanosleep(300);
              trap_if(++it > (1u << 22));
            }
            fence_async();
            __syncwarp();
          }
          cnt++;
        }
      }
      if (lane == 0) asm volatile("st.release.cta.shared.u32 [%0], %1;" ::"r"(bars + W_CLEAR), "r"(cnt) : "memory");
    } else if (warp > 0) {
      const uint32_t w = warp - 1;
      const uint32_t stg = sbase + OFF_STG + w * 16384;
      if (warp == 1 && elect_one()) {
#pragma unroll
        for (int s = 0; s < STAGES; s++) mbar_init(bars + B_EMPTY + 8 * s, 8);
#pragma unroll
        for (int s = 0; s < 4; s++) { mbar_init(bars + B_SFULL + 8 * s, 4); mbar_init(bars + B_SEMPTY + 8 * s, 1); }
        mbar_init(bars + B_RECV, 1); mbar_init(bars + B_RECV + 8, 1);
#pragma unroll
        for (int s = 0; s < 10; s++) mbar_init(bars + B_GLOAD + 8 * s, 1);
        asm volatile("st.shared.u32 [%0], %1;" ::"r"(bars + W_CLEAR), "r"(0) : "memory");
        asm volatile("fence.mbarrier_init.release.cluster;" ::: "memory");
        fence_async_smem();
      }
      __syncwarp();
      asm volatile("bar.sync 1, 384;" ::: "memory");
      asm volatile("barrier.cluster.arrive.relaxed.aligned;" ::: "memory");
      if (b < 128) {
        const int row0 = SEG_M(seg0) * 128 + SEG_IDX(seg0) * 16 + w * 8;
        float zrow = 0.f;
        const uint4* wp = ptr_add(p.gw, lane * 16);
        const uint4* xp = p.x + row0 * 128;
        uint4 wv[4];
#pragma unroll
        for (int i = 0; i < 4; i++) wv[i] = __ldg(wp + i * 32);
        mbar_wait(bars + B_FULL + 8 * GWAIT, 0);
#define GATE_LOAD(r)                                                                                               \
  if (lane == 0) {                                                                                                 \
    const uint32_t gb = bars + B_GLOAD + 16 * w + 4 * ((r) & 2);                                                   \
    mbar_expect(gb, 4096);                                                                                         \
    asm volatile("cp.async.bulk.shared::cluster.global.mbarrier::complete_tx::bytes [%0], [%1], 4096, [%2];"      \
                 ::"r"(stg + (r) * 2048), "l"(ptr_add(xp, (r) * 2048)), "r"(gb) : "memory");                       \
  }
        GATE_LOAD(0)
#pragma unroll 1
        for (int r = 0; r < 8; r += 2) {
          mbar_wait(bars + B_GLOAD + 16 * w + 4 * (r & 2), (r >> 2) & 1);
          if (r < 6) GATE_LOAD(r + 2)
          float z0 = 0.f, z1 = 0.f, y0 = 0.f, y1 = 0.f;
#pragma unroll
          for (int i = 0; i < 4; i++) {
            uint32_t a[4], c[4];
            asm volatile("ld.shared.v4.u32 {%0,%1,%2,%3}, [%4];" : "=r"(a[0]), "=r"(a[1]), "=r"(a[2]), "=r"(a[3])
                         : "r"(stg + r * 2048 + i * 512 + lane * 16) : "memory");
            asm volatile("ld.shared.v4.u32 {%0,%1,%2,%3}, [%4+2048];" : "=r"(c[0]), "=r"(c[1]), "=r"(c[2]), "=r"(c[3])
                         : "r"(stg + r * 2048 + i * 512 + lane * 16) : "memory");
            const uint32_t wq4[4] = {wv[i].x, wv[i].y, wv[i].z, wv[i].w};
#pragma unroll
            for (int e = 0; e < 4; e++) {
              z0 = fmaf(bf_lo(a[e]), bf_lo(wq4[e]), z0); z1 = fmaf(bf_hi(a[e]), bf_hi(wq4[e]), z1);
              y0 = fmaf(bf_lo(c[e]), bf_lo(wq4[e]), y0); y1 = fmaf(bf_hi(c[e]), bf_hi(wq4[e]), y1);
            }
          }
          float z = z0 + z1, y = y0 + y1;
          const float keep = lane < 16 ? z : y, give = lane < 16 ? y : z;
          z = keep + __shfl_xor_sync(0xffffffff, give, 16);
#pragma unroll
          for (int o = 8; o > 0; o >>= 1) z += __shfl_xor_sync(0xffffffff, z, o);
          if ((lane & 15) == r + (lane >> 4)) zrow = z;
        }
        const float ic = 1.f + ex2f(zrow * 1.4426950408889634f);
        const float g = rcpf(1.f + ex2f(zrow * -1.4426950408889634f));
        if ((lane & 15) < 8 && (lane & 1) == (lane >> 4)) *ptr_add(p.sync->gate, (row0 + (lane & 15)) * 8) = make_float2(g, ic > 1e38f ? 1e38f : ic);
        __syncwarp();
        if (lane == 0) red_release(&p.sync->gatecnt[0]);
      }
      asm volatile("barrier.cluster.wait.aligned;" ::: "memory");
      if (elect_one()) {
        uint32_t ep, fph = 0, mine = w ^ 1, tph = w ^ 1;
        mbar_wait(bars + B_EPOCH, 0);
        asm volatile("ld.shared.u32 %0, [%1];" : "=r"(ep) : "r"(bars + W_EPOCH) : "memory");
        for (int si = 0;; si++) {
          const uint32_t seg = c_sched.s[b][si];
          const uint32_t epi = SEG_EPI(seg), m = SEG_M(seg), idx = SEG_IDX(seg);
          if (SEG_TYPE(seg) == T_END) break;
          if (epi == E_NONE) continue;
          if (epi == E_SEND) {
            if (mine) {
              if (SEG_EPI(c_sched.s[b][si + 1]) == E_FINRED) {
                poll_ge(ptr_add(p.sync->hflag, (m * 4 + idx) * 4), ep);
                fence_async();
              }
              mbar_arrive(bars + B_HOK);
            } else {
              mbar_expect(bars + B_RECV, 16384);
              mbar_expect(bars + B_RECV + 8, 16384);
              mbar_arrive_remote(map_peer(bars + B_PEER, (b & 1) ^ 1));
            }
            break;
          }
          mine ^= 1;
          if (mine) {
            if (epi == E_GU) fph ^= 1;
            continue;
          }
          mbar_wait(bars + B_TURN + 8 * w, tph);
          tph ^= 1;
          if (SEG_TYPE(c_sched.s[b][si + 1]) == T_END) {
            mbar_wait(bars + B_SFULL, fph);
            mbar_wait(bars + B_SFULL + 16, fph);
            red_release(ptr_add(p.sync->flags, (512 + m * 4 + idx) * 4));
            break;
          }
          const uint32_t nsb = epi == E_GU ? 2 : 4;
          uint32_t row, flag;
          if (epi == E_PQ) { row = (m * KZ + idx * 4) * 128; flag = m * 32 + (idx >> 2); }
          else if (epi == E_GU) { row = (m * KZ + 32 + idx * 2) * 128; flag = m * 32 + 2 + idx; }
          else { row = m * 128; flag = 512 + m * 4 + idx; }
#pragma unroll 1
          for (uint32_t sb = 0; sb < nsb; sb++) {
            const uint32_t buf = sb & 1;
#pragma unroll 1
            for (uint32_t g = 0; g < 2; g++) {
              const uint32_t src = sbase + OFF_STG + g * 16384 + buf * 8192;
              mbar_wait(bars + B_SFULL + g * 16 + 8 * buf, fph);
              if (epi == E_HELP) {
#pragma unroll
                for (int q = 0; q < 4; q++) tma_store(&p.outm, src + q * 2048, idx * 256 + sb * 64, row + g * 64 + q * 16);
              } else {
                tma_store(&p.zst, src, 0, row + sb * 128 + g * 64);
              }
            }
            bulk_commit();
            bulk_wait_read();
            mbar_arrive(bars + B_SEMPTY + 8 * buf);
            mbar_arrive(bars + B_SEMPTY + 16 + 8 * buf);
            fph ^= buf;
          }
          mbar_arrive(bars + B_TURN + 8 * (w ^ 1));
          bulk_wait();
          red_release(ptr_add(p.sync->flags, flag * 4));
        }
      }
    } else {
      if (elect_one()) {
        PROF(1);
        const bool pq = b < 128;
        const int idx = SEG_IDX(seg0), row = SEG_M(seg0) * 128, c0 = pq ? (idx & 3) * 4 : idx * 2, c1 = pq ? c0 + 2 : c0;
        const CUtensorMap* ma = &p.sre + (pq ? idx >> 2 : 2);
        const CUtensorMap* mb0 = &p.xb + (pq ? 0 : 1);
        const CUtensorMap* mb1 = &p.xb + (pq ? 0 : 2);
#pragma unroll 1
        for (int s = 0; s < STAGES; s++) {
          const uint32_t fb = bars + B_FULL + 8 * s, sa = sbase + s * ST_BYTES;
          mbar_init(fb, 1);
          if (PRO) asm volatile("fence.mbarrier_init.release.cluster;" ::: "memory");
          else fence_async_smem();
          mbar_expect(fb, ST_BYTES);
          tma2d(sa, ma, s * 64, row, fb, POL_NORMAL);
          tma3d(sa + A_BYTES, mb0, 0, s * 64, c0, fb, POL_NORMAL);
          tma3d(sa + A_BYTES + 16384, mb1, 0, s * 64, c1, fb, POL_NORMAL);
          if (PSET == 1) PROF(40 + s);
          if (SDELAY && s == 0) { const long long t0 = clock64(); while (clock64() - t0 < SDELAY); }
        }
      }
      __syncwarp();
      asm volatile("bar.arrive 1, 384;" ::: "memory");
      asm volatile("barrier.cluster.arrive.relaxed.aligned;" ::: "memory");
      asm volatile("barrier.cluster.wait.aligned;" ::: "memory");
      if (elect_one()) {
        uint32_t seg = seg0 + (STAGES << 12) - (STAGES << 19);
        uint32_t st = 0, ph = 0, cnt = 0, cleared = 0;
#define WAIT_CLEARED()                                                                                            \
  {                                                                                                               \
    uint32_t it = 0;                                                                                              \
    while (cleared <= cnt) {                                                                                      \
      asm volatile("ld.acquire.cta.shared.u32 %0, [%1];" : "=r"(cleared) : "r"(bars + W_CLEAR) : "memory");     \
      trap_if(++it > (1u << 26));                                                                                 \
    }                                                                                                             \
    cnt++;                                                                                                        \
  }
        for (int si = 1; SEG_TYPE(seg) != T_END; si++) {
          const uint32_t type = SEG_TYPE(seg);
          int nk = SEG_NK(seg);
          Loads l = seg_loads(p, seg);
          if (type == T_OUTB) {
            for (int q = 3; q < 5; q++)
              asm volatile("cp.async.bulk.prefetch.tensor.3d.L2.global [%0, {%1, %2, %3}];" ::"l"(l.mb0), "r"(0), "r"(l.b1 + q * 64), "r"(l.c0) : "memory");
#pragma unroll 1
            for (int slot = 0; slot < 12; slot += 3) {
              mbar_wait(bars + B_EMPTY + 8 * st, ph);
              if (slot == 0) PROF(7 + si);
              const uint32_t fb = bars + B_FULL + 8 * st;
              mbar_expect(fb, slot < 9 ? ST_BYTES : 16384);
#pragma unroll 1
              for (int r = 0; r < 3 && slot + r < 2 * NBETA; r++) {
                const uint32_t dst = sbase + st * ST_BYTES + r * 16384;
                if ((slot + r) & 1) { tma3d(dst, l.mb0, 0, l.b1, l.c0, fb, l.pb); l.b1 += 64; }
                else { WAIT_CLEARED(); tma2d(dst, l.ma, 0, l.a1, fb, l.pa); l.a1 += 128; }
              }
              if (++st == STAGES) { st = 0; ph ^= 1; }
            }
            break;
          }
#pragma unroll 1
          for (; nk > 0; nk--) {
            if (type >= T_OUTM) WAIT_CLEARED();
            mbar_wait(bars + B_EMPTY + 8 * st, ph);
            issue_loads(l, sbase + st * ST_BYTES, bars + B_FULL + 8 * st);
            if (++st == STAGES) { st = 0; ph ^= 1; }
          }
          seg = c_sched.s[b][si];
        }
      }
    }
  }
}

typedef CUresult (*EncodeFn)(CUtensorMap*, CUtensorMapDataType, cuuint32_t, void*, const cuuint64_t*, const cuuint64_t*,
                             const cuuint32_t*, const cuuint32_t*, CUtensorMapInterleave, CUtensorMapSwizzle,
                             CUtensorMapL2promotion, CUtensorMapFloatOOBfill);

#define L2PROM CU_TENSOR_MAP_L2_PROMOTION_L2_128B

void map2d(EncodeFn enc, CUtensorMap* m, const void* ptr, uint64_t inner, uint64_t outer, uint32_t rows, bool swz,
           CUtensorMapL2promotion prom = L2PROM) {
  cuuint64_t dims[2] = {inner, outer}, str[1] = {inner * 2};
  cuuint32_t box[2] = {64, rows}, es[2] = {1, 1};
  enc(m, CU_TENSOR_MAP_DATA_TYPE_BFLOAT16, 2, (void*)ptr, dims, str, box, es, CU_TENSOR_MAP_INTERLEAVE_NONE,
      swz ? CU_TENSOR_MAP_SWIZZLE_128B : CU_TENSOR_MAP_SWIZZLE_NONE, prom, CU_TENSOR_MAP_FLOAT_OOB_FILL_NONE);
}
void map3k(EncodeFn enc, CUtensorMap* m, const void* ptr, uint64_t K, uint64_t N) {
  cuuint64_t dims[3] = {K, N, 1}, str[2] = {K * 2, K * N * 2};
  cuuint32_t box[3] = {64, 128, 1}, es[3] = {1, 1, 1};
  enc(m, CU_TENSOR_MAP_DATA_TYPE_BFLOAT16, 3, (void*)ptr, dims, str, box, es, CU_TENSOR_MAP_INTERLEAVE_NONE,
      CU_TENSOR_MAP_SWIZZLE_128B, L2PROM, CU_TENSOR_MAP_FLOAT_OOB_FILL_NONE);
}
void map3d(EncodeFn enc, CUtensorMap* m, const void* ptr, uint64_t N, uint64_t K, uint32_t chunks) {
  cuuint64_t dims[3] = {64, K, N / 64}, str[2] = {N * 2, 128};
  cuuint32_t box[3] = {64, 64, chunks}, es[3] = {1, 1, 1};
  enc(m, CU_TENSOR_MAP_DATA_TYPE_BFLOAT16, 3, (void*)ptr, dims, str, box, es, CU_TENSOR_MAP_INTERLEAVE_NONE,
      CU_TENSOR_MAP_SWIZZLE_128B, L2PROM, CU_TENSOR_MAP_FLOAT_OOB_FILL_NONE);
}

}

extern "C" void kernel_launch(void* const* d_in, const int* in_sizes, int n_in, void* d_out, int out_size) {
  (void)in_sizes; (void)n_in; (void)out_size;
  EncodeFn enc = nullptr;
  cudaDriverEntryPointQueryResult q;
  cudaGetDriverEntryPoint("cuTensorMapEncodeTiled", (void**)&enc, cudaEnableDefault, &q);
  void *z = nullptr, *sy = nullptr;
  cudaGetSymbolAddress(&z, g_Z);
  cudaGetSymbolAddress(&sy, g_sync);
  Params p;
  map2d(enc, &p.sre, d_in[1], SEQ, SEQ, 128, true, PROMS);
  map2d(enc, &p.sim, d_in[2], SEQ, SEQ, 128, true, PROMS);
  map2d(enc, &p.xa, d_in[0], DM, SEQ, 128, true);
  map3d(enc, &p.xb, d_in[0], DM, SEQ, 2);
  map3d(enc, &p.wg, d_in[6], FF, DM, 2);
  map3d(enc, &p.wu, d_in[7], FF, DM, 2);
  map3k(enc, &p.hre, d_in[3], DM, DM);
  map3k(enc, &p.him, d_in[4], DM, DM);
  map3d(enc, &p.wd, d_in[8], DM, FF, 2);
  map2d(enc, &p.zld, z, 64, ZROWS, 128, false);
  map2d(enc, &p.zst, z, 64, ZROWS, 64, false);
  map2d(enc, &p.outm, d_out, DM, SEQ, 16, true);
  p.x = (const uint4*)d_in[0];
  p.gw = (const uint4*)d_in[9];
  p.sync = (Sync*)sy;
  p.out = (uint4*)d_out;
  for (int b = 0; b < 132; b++) p.first[b] = first_seg(b);
  p.prof = nullptr;
  cudaFuncSetAttribute(fused_kernel, cudaFuncAttributeMaxDynamicSharedMemorySize, SMEM_BYTES);
  fused_kernel<<<NCTA, 384, SMEM_BYTES>>>(p);
}
```

```cpp
#include <cuda_runtime.h>
#include <cuda_bf16.h>
#include <cuda.h>
#include <stdint.h>

namespace {

constexpr int SEQ = 2048, DM = 1024, FF = 3584;
constexpr int KZ = 88;
constexpr int ZROWS = 16 * KZ * 128;
constexpr int NBETA = 5;

constexpr int STAGES = 4;
constexpr int A_BYTES = 128 * 64 * 2, B_BYTES = 256 * 64 * 2, ST_BYTES = A_BYTES + B_BYTES;
constexpr int OFF_STG = STAGES * ST_BYTES;
constexpr int OFF_BAR = OFF_STG + 32768;
constexpr int SMEM_BYTES = OFF_BAR + 256 + 1024;
constexpr int B_FULL = 0, B_EMPTY = 32, B_SFULL = 64, B_SEMPTY = 96, B_RECV = 128, B_GLOAD = 144, B_PEER = 176, B_HOK = 184,
              B_GREADY = 192, B_EPOCH = 200, B_TURN = 208, W_EPOCH = 224, W_CLEAR = 228;

enum { T_END = 0, T_PQ = 1, T_GU = 2, T_OUTM = 3, T_OUTK = 4, T_OUTB = 5 };
enum { E_NONE = 0, E_GU = 1, E_PQ = 2, E_HELP = 3, E_SEND = 4, E_FIN = 5, E_FINRED = 6 };

constexpr uint32_t mkseg(int type, int m, int idx, int k0, int nk, int flag, int epi) {
  return (uint32_t)type | ((uint32_t)m << 3) | ((uint32_t)idx << 7) | ((uint32_t)k0 << 12) | ((uint32_t)nk << 19) |
         ((uint32_t)flag << 27) | ((uint32_t)epi << 28);
}
#define SEG_TYPE(s) ((s) & 7u)
#define SEG_M(s) (((s) >> 3) & 15u)
#define SEG_IDX(s) (((s) >> 7) & 31u)
#define SEG_K0(s) (((s) >> 12) & 127u)
#define SEG_NK(s) (((s) >> 19) & 127u)
#define SEG_FLAG(s) (((s) >> 27) & 1u)
#define SEG_EPI(s) (((s) >> 28) & 7u)

constexpr int NCTA = 132;
constexpr int MAXSEG = 16;
struct Sched { uint32_t s[132][MAXSEG]; };

constexpr int cl_g(int c) { return c < 4 ? 0 : c < 36 ? (c - 4) % 8 : 1 + (c - 36) % 7; }
constexpr int cl_r(int c) { return c < 4 ? 4 + c : c < 36 ? (c - 4) / 8 : 4 + (c - 36) / 7; }
constexpr int cl_pair(int c) { const int t[8] = {0, 2, 1, 1, 3, 0, 3, 2}; return t[cl_g(c)]; }
constexpr int cl_half(int c) { const int t[8] = {0, 0, 0, 1, 0, 1, 1, 1}; return t[cl_g(c)]; }
constexpr uint32_t first_seg(int b) {
  const int g = cl_g(b >> 1), r = cl_r(b >> 1);
  return b < 128 ? mkseg(T_PQ, (b & 1) + 2 * ((g & 6) + (r >> 2)), 4 * (g & 1) + (r & 3), 0, 32, 0, E_PQ)
                 : mkseg(T_GU, (b - 128) * 4, 19, 0, 16, 0, E_GU);
}

constexpr Sched make_sched() {
  Sched t{};
  const int r3[4] = {19, 20, 26, 27};
  for (int b = 0; b < 128; b++) {
    const int pr = cl_pair(b >> 1), h = cl_half(b >> 1), rk = cl_r(b >> 1), r = b & 1;
    int m = r + 2 * (4 * h + (rk >> 1)), c = 0;
    const int j = 2 * pr + (rk & 1);
    t.s[b][c++] = first_seg(b);
    t.s[b][c++] = mkseg(T_GU, m, j < 3 ? j : 18 + j, 0, 16, 0, E_GU);
    t.s[b][c++] = mkseg(T_GU, m, 3 + j, 12, 16, 1, E_GU);
    t.s[b][c++] = mkseg(T_GU, m, 11 + j, 8, 16, 1, E_GU);
    m = (pr & 1) + 2 * (4 * (pr >> 1) + (rk >> 1));
    const int n = 2 * h + (rk & 1);
    if (!r) {
      t.s[b][c++] = mkseg(T_OUTM, m, n, 32, 14, 0, E_NONE);
      t.s[b][c++] = mkseg(T_OUTK, m, n, 0, 16, 0, E_NONE);
      t.s[b][c++] = mkseg(T_OUTK, m, n, 16, 16, 0, E_SEND);
    } else if (n == 0) {
      t.s[b][c++] = mkseg(T_OUTM, m, 1, 74, 9, 0, E_HELP);
      t.s[b][c++] = mkseg(T_OUTM, m, 0, 76, 7, 1, E_NONE);
      t.s[b][c++] = mkseg(T_OUTM, m, 0, 46, 30, 1, E_SEND);
    } else {
      t.s[b][c++] = mkseg(T_GU, m, r3[n], 0, 16, 0, E_GU);
      t.s[b][c++] = mkseg(T_OUTM, m, n, 46, n == 1 || (n == 2 && (m & 3) == 0) ? 28 : 30, 1, E_SEND);
    }
    t.s[b][c++] = mkseg(T_OUTB, m, n, KZ - NBETA, NBETA, r, n == 0 ? E_FIN : E_FINRED);
  }
  for (int e = 0; e < 4; e++) {
    int c = 0;
    for (int q = 0; q < 4; q++) t.s[128 + e][c++] = mkseg(T_GU, 4 * e + q, r3[0], 0, 16, 0, E_GU);
    for (int q = 0; q < 8; q++) t.s[128 + e][c++] = mkseg(T_OUTM, 4 * e + (q & 3), 2 + (q >> 2), q ? 76 : 74, q ? 7 : 9, 0, E_HELP);
  }
  return t;
}
constexpr bool sched_ok(const Sched& t) {
  int z[16][36] = {}, o[16][8][KZ] = {};
  for (int b = 0; b < NCTA; b++)
    for (int c = 0; SEG_TYPE(t.s[b][c]) != T_END; c++) {
      const uint32_t s = t.s[b][c];
      if (SEG_TYPE(s) <= T_GU) z[SEG_M(s)][SEG_IDX(s) + (SEG_TYPE(s) == T_GU ? 8 : 0)]++;
      else
        for (uint32_t k = SEG_K0(s); k < SEG_K0(s) + SEG_NK(s); k++)
          for (uint32_t hf = 0; hf < 2; hf++)
            if (SEG_TYPE(s) != T_OUTB || hf == SEG_FLAG(s)) o[SEG_M(s)][SEG_IDX(s) * 2 + hf][k]++;
    }
  for (int m = 0; m < 16; m++) {
    for (int i = 0; i < 36; i++) if (z[m][i] != 1) return false;
    for (int i = 0; i < 8; i++) for (int k = 0; k < KZ; k++) if (o[m][i][k] != 1) return false;
  }
  return true;
}
static_assert(sched_ok(make_sched()), "schedule does not cover the problem");
__constant__ Sched c_sched = make_sched();

struct Sync {
  float2 gate[SEQ];
  unsigned flags[16 * 32];
  unsigned hflag[128];
  unsigned epoch[160];
  unsigned gatecnt[32];
};
struct Params {
  const uint4* x;
  const uint4* gw;
  Sync* sync;
  uint4* out;
  uint2 first[132];
  CUtensorMap sre, sim, xa, xb, wg, wu, hre, him, wd, zld, zst, outm;
};

__device__ __align__(1024) __nv_bfloat16 g_Z[(size_t)ZROWS * 64];
__device__ __align__(128) Sync g_sync;

__device__ __forceinline__ uint32_t smem_u32(const void* p) { return (uint32_t)__cvta_generic_to_shared(p); }
__device__ __forceinline__ void mbar_init(uint32_t a, uint32_t c) {
  asm volatile("mbarrier.init.shared::cta.b64 [%0], %1;" ::"r"(a), "r"(c) : "memory");
}
__device__ __forceinline__ void mbar_expect(uint32_t a, uint32_t bytes) {
  asm volatile("mbarrier.arrive.expect_tx.shared::cta.b64 _, [%0], %1;" ::"r"(a), "r"(bytes) : "memory");
}
__device__ __forceinline__ void mbar_arrive(uint32_t a) {
  asm volatile("mbarrier.arrive.shared::cta.b64 _, [%0];" ::"r"(a) : "memory");
}
__device__ __forceinline__ void mbar_wait(uint32_t a, uint32_t parity) {
  asm volatile(
      "{ .reg .pred p; .reg .u32 it;\n"
      "mov.u32 it, 0;\n"
      "WAIT_LOOP:\n"
      "mbarrier.try_wait.parity.shared::cta.b64 p, [%0], %1;\n"
      "@p bra WAIT_DONE;\n"
      "add.u32 it, it, 1;\n"
      "setp.lt.u32 p, it, 0x100000;\n"
      "@p bra WAIT_LOOP;\n"
      "trap;\n"
      "WAIT_DONE:\n"
      "}" ::"r"(a), "r"(parity) : "memory");
}
__device__ __forceinline__ void mbar_wait_cluster(uint32_t a, uint32_t parity) {
  asm volatile(
      "{ .reg .pred p; .reg .u32 it;\n"
      "mov.u32 it, 0;\n"
      "WAIT_LOOP:\n"
      "mbarrier.try_wait.parity.relaxed.cluster.shared::cta.b64 p, [%0], %1;\n"
      "@p bra WAIT_DONE;\n"
      "add.u32 it, it, 1;\n"
      "setp.lt.u32 p, it, 0x100000;\n"
      "@p bra WAIT_LOOP;\n"
      "trap;\n"
      "WAIT_DONE:\n"
      "fence.acquire.sync_restrict::shared::cluster.cluster;\n"
      "}" ::"r"(a), "r"(parity) : "memory");
}
__device__ __forceinline__ bool mbar_test(uint32_t a, uint32_t parity) {
  uint32_t ok;
  asm volatile("{ .reg .pred p; mbarrier.test_wait.parity.shared::cta.b64 p, [%1], %2; selp.u32 %0, 1, 0, p; }"
               : "=r"(ok) : "r"(a), "r"(parity) : "memory");
  return ok;
}
__device__ __forceinline__ void trap_if(bool c) {
  asm volatile("{ .reg .pred p; setp.ne.u32 p, %0, 0; @p trap; }" ::"r"((uint32_t)c));
}
template <typename T>
__device__ __forceinline__ T* ptr_add(T* base, uint32_t bytes) {
  uint64_t r;
  asm("{ .reg .u32 lo, hi; mov.b64 {lo, hi}, %1; add.cc.u32 lo, lo, %2; addc.u32 hi, hi, 0; mov.b64 %0, {lo, hi}; }"
      : "=l"(r) : "l"(base), "r"(bytes));
  return (T*)r;
}
__device__ __forceinline__ unsigned ld_acquire(const unsigned* p) {
  unsigned v;
  asm volatile("ld.acquire.gpu.global.u32 %0, [%1];" : "=r"(v) : "l"(p) : "memory");
  return v;
}
__device__ __forceinline__ unsigned ld_relaxed(const unsigned* p) {
  unsigned v;
  asm volatile("ld.relaxed.gpu.global.u32 %0, [%1];" : "=r"(v) : "l"(p) : "memory");
  return v;
}
__device__ __forceinline__ void red_release(unsigned* p) {
  asm volatile("red.release.gpu.global.add.u32 [%0], 1;" ::"l"(p) : "memory");
}
__device__ __forceinline__ void poll_ge(const unsigned* p, unsigned target) {
  uint32_t it = 0;
  while ((int)(ld_relaxed(p) - target) < 0) {
    __nanosleep(40);
    trap_if(++it > (1u << 22));
  }
  (void)ld_acquire(p);
}
__device__ __forceinline__ void fence_async() { asm volatile("fence.proxy.async.global;" ::: "memory"); }
__device__ __forceinline__ void fence_async_smem() { asm volatile("fence.proxy.async.shared::cta;" ::: "memory"); }
constexpr uint64_t POL_NORMAL = 0x1000000000000000ull, POL_FIRST = 0x12F0000000000000ull;
__device__ __forceinline__ void tma2d(uint32_t dst, const CUtensorMap* m, int c0, int c1, uint32_t bar, uint64_t pol) {
  asm volatile("cp.async.bulk.tensor.2d.shared::cluster.global.mbarrier::complete_tx::bytes.L2::cache_hint [%0], [%1, {%3, %4}], [%2], %5;"
               ::"r"(dst), "l"(m), "r"(bar), "r"(c0), "r"(c1), "l"(pol) : "memory");
}
__device__ __forceinline__ void tma3d(uint32_t dst, const CUtensorMap* m, int c0, int c1, int c2, uint32_t bar, uint64_t pol) {
  asm volatile("cp.async.bulk.tensor.3d.shared::cluster.global.mbarrier::complete_tx::bytes.L2::cache_hint [%0], [%1, {%3, %4, %5}], [%2], %6;"
               ::"r"(dst), "l"(m), "r"(bar), "r"(c0), "r"(c1), "r"(c2), "l"(pol) : "memory");
}
__device__ __forceinline__ void tma_store(const CUtensorMap* m, uint32_t src, int c0, int c1) {
  asm volatile("cp.async.bulk.tensor.2d.global.shared::cta.bulk_group [%0, {%2, %3}], [%1];"
               ::"l"(m), "r"(src), "r"(c0), "r"(c1) : "memory");
}
__device__ __forceinline__ uint32_t map_peer(uint32_t a, uint32_t cta) {
  uint32_t r;
  asm("mapa.shared::cluster.u32 %0, %1, %2;" : "=r"(r) : "r"(a), "r"(cta));
  return r;
}
__device__ __forceinline__ void mbar_arrive_remote(uint32_t a) {
  asm volatile("fence.release.sync_restrict::shared::cta.cluster;\n"
               "mbarrier.arrive.relaxed.cluster.shared::cluster.b64 _, [%0];" ::"r"(a) : "memory");
}
__device__ __forceinline__ void bulk_commit() { asm volatile("cp.async.bulk.commit_group;" ::: "memory"); }
__device__ __forceinline__ void bulk_wait_read() { asm volatile("cp.async.bulk.wait_group.read 0;" ::: "memory"); }
__device__ __forceinline__ void bulk_wait() { asm volatile("cp.async.bulk.wait_group 0;" ::: "memory"); }
__device__ __forceinline__ void prefetch_map(const CUtensorMap* m) {
  asm volatile("prefetch.tensormap [%0];" ::"l"(m) : "memory");
}
__device__ __forceinline__ bool elect_one() {
  uint32_t p;
  asm volatile("{ .reg .pred p; elect.sync _|p, 0xffffffff; selp.u32 %0, 1, 0, p; }" : "=r"(p));
  return p;
}
__device__ __forceinline__ void stsm4(uint32_t a, uint32_t r0, uint32_t r1, uint32_t r2, uint32_t r3) {
  asm volatile("stmatrix.sync.aligned.m8n8.x4.shared.b16 [%0], {%1,%2,%3,%4};" ::"r"(a), "r"(r0), "r"(r1), "r"(r2), "r"(r3) : "memory");
}
__device__ __forceinline__ uint32_t pack2(float lo, float hi) {
  uint32_t r;
  asm("cvt.rn.bf16x2.f32 %0, %1, %2;" : "=r"(r) : "f"(hi), "f"(lo));
  return r;
}
__device__ __forceinline__ float bf_lo(uint32_t v) { return __uint_as_float(v << 16); }
__device__ __forceinline__ float bf_hi(uint32_t v) { return __uint_as_float(v & 0xffff0000u); }
__device__ __forceinline__ float ex2f(float x) { float r; asm("ex2.approx.ftz.f32 %0, %1;" : "=f"(r) : "f"(x)); return r; }
__device__ __forceinline__ float rcpf(float x) { float r; asm("rcp.approx.ftz.f32 %0, %1;" : "=f"(r) : "f"(x)); return r; }

#define R8(d, i) "+f"(d[i]), "+f"(d[i + 1]), "+f"(d[i + 2]), "+f"(d[i + 3]), "+f"(d[i + 4]), "+f"(d[i + 5]), "+f"(d[i + 6]), "+f"(d[i + 7])
#define R64LO(d) R8(d, 0), R8(d, 8), R8(d, 16), R8(d, 24), R8(d, 32), R8(d, 40), R8(d, 48), R8(d, 56)
#define R64HI(d) R8(d, 64), R8(d, 72), R8(d, 80), R8(d, 88), R8(d, 96), R8(d, 104), R8(d, 112), R8(d, 120)
#define S64LO "%0,%1,%2,%3,%4,%5,%6,%7,%8,%9,%10,%11,%12,%13,%14,%15,%16,%17,%18,%19,%20,%21,%22,%23,%24,%25,%26,%27,%28,%29,%30,%31," \
              "%32,%33,%34,%35,%36,%37,%38,%39,%40,%41,%42,%43,%44,%45,%46,%47,%48,%49,%50,%51,%52,%53,%54,%55,%56,%57,%58,%59,%60,%61,%62,%63"
#define S64HI "%64,%65,%66,%67,%68,%69,%70,%71,%72,%73,%74,%75,%76,%77,%78,%79,%80,%81,%82,%83,%84,%85,%86,%87,%88,%89,%90,%91,%92,%93,%94,%95," \
              "%96,%97,%98,%99,%100,%101,%102,%103,%104,%105,%106,%107,%108,%109,%110,%111,%112,%113,%114,%115,%116,%117,%118,%119,%120,%121,%122,%123,%124,%125,%126,%127"

constexpr uint32_t DESC_HI = 0x40000040u;
__device__ __forceinline__ uint64_t mkdesc(uint32_t lo) { return ((uint64_t)DESC_HI << 32) | lo; }

template <int TB>
__device__ __forceinline__ void wgmma256(float (&d)[128], uint32_t da, uint32_t db, uint32_t acc) {
  asm volatile("{ .reg .pred p; setp.ne.b32 p, %130, 0;\n"
               "wgmma.mma_async.sync.aligned.m64n256k16.f32.bf16.bf16 {" S64LO "," S64HI "}, %128, %129, p, 1, 1, 0, %131; }"
               : R64LO(d), R64HI(d) : "l"(mkdesc(da)), "l"(mkdesc(db)), "r"(acc), "n"(TB));
}
__device__ __forceinline__ void wgmma128(float (&d)[128], uint32_t da, uint32_t db) {
  asm volatile("wgmma.mma_async.sync.aligned.m64n128k16.f32.bf16.bf16 {" S64LO "}, %64, %65, 1, 1, 1, 0, 1;"
               : R64LO(d) : "l"(mkdesc(da)), "l"(mkdesc(db)));
}
__device__ __forceinline__ void wg_fence() { asm volatile("wgmma.fence.sync.aligned;" ::: "memory"); }
__device__ __forceinline__ void wg_commit() { asm volatile("wgmma.commit_group.sync.aligned;" ::: "memory"); }
__device__ __forceinline__ void wg_wait_all(float (&d)[128]) {
  asm volatile("wgmma.wait_group.sync.aligned 0;" : R64LO(d), R64HI(d)::"memory");
}
__device__ __forceinline__ void wg_wait_lo(float (&d)[128]) {
  asm volatile("wgmma.wait_group.sync.aligned 0;" : R64LO(d)::"memory");
}

__device__ __forceinline__ void stage_done(uint32_t bar) {
  fence_async_smem();
  __syncwarp();
  if (elect_one()) mbar_arrive(bar);
}

template <int C>
__device__ __forceinline__ void gu_chunk(uint32_t (&pk)[64], float ic0, float ic1, uint32_t sa) {
  uint32_t o[4];
#pragma unroll
  for (int r = 0; r < 4; r++) {
    asm volatile("" : "+r"(pk[4 * C + r]), "+r"(pk[32 + 4 * C + r]));
    const uint32_t G = pk[4 * C + r], U = pk[32 + 4 * C + r];
    const float ic = (r & 1) ? ic1 : ic0;
    const float e0 = ex2f(bf_lo(G) * -1.4426950408889634f), e1 = ex2f(bf_hi(G) * -1.4426950408889634f);
    o[r] = pack2(bf_lo(U) * rcpf(fmaf(e0, ic, ic)), bf_hi(U) * rcpf(fmaf(e1, ic, ic)));
  }
  stsm4((sa + (C >> 2) * 8192) ^ ((C & 3) << 5), o[0], o[1], o[2], o[3]);
}
template <int C>
__device__ __forceinline__ void plain_chunk(uint32_t (&pk)[64], float m0, float m1, uint32_t sa) {
#pragma unroll
  for (int jj = 0; jj < 4; jj++) {
    uint32_t o[4];
#pragma unroll
    for (int r = 0; r < 4; r++) {
      asm volatile("" : "+r"(pk[16 * C + 4 * jj + r]));
      const uint32_t v = pk[16 * C + 4 * jj + r];
      const float m = (r & 1) ? m1 : m0;
      o[r] = pack2(bf_lo(v) * m, bf_hi(v) * m);
    }
    stsm4((sa + (C & 1) * 8192) ^ (jj << 5), o[0], o[1], o[2], o[3]);
  }
}

struct Loads {
  const CUtensorMap *ma, *mb0, *mb1;
  int a0, a1, da0, da1, b0, b1, db0, db1, c0, c1, e1, wrap;
  uint64_t pa, pb;
};
__device__ __forceinline__ Loads seg_loads(const Params& p, uint32_t seg) {
  const int type = SEG_TYPE(seg), m = SEG_M(seg), idx = SEG_IDX(seg), k0 = SEG_K0(seg), swap = SEG_FLAG(seg);
  Loads l;
  l.pa = type == T_GU ? POL_NORMAL : POL_FIRST;
  l.pb = type == T_PQ ? POL_NORMAL : POL_FIRST;
  l.wrap = type == T_GU ? DM - 1 : -1;
  if (type <= T_GU) {
    l.a0 = k0 * 64; l.a1 = m * 128; l.da0 = 64; l.da1 = 0;
    l.b0 = 0; l.b1 = k0 * 64; l.db0 = 0; l.db1 = 64; l.e1 = 0;
    if (type == T_PQ) { l.ma = idx < 4 ? &p.sre : &p.sim; l.mb0 = l.mb1 = &p.xb; l.c0 = (idx & 3) * 4; l.c1 = l.c0 + 2; }
    else { l.ma = &p.xa; l.mb0 = &p.wg; l.mb1 = &p.wu; l.c0 = l.c1 = idx * 2; }
  } else {
    l.ma = &p.zld; l.a0 = 0; l.a1 = (m * KZ + k0) * 128; l.da0 = 0; l.da1 = 128;
    if (type == T_OUTK) {
      l.mb0 = l.mb1 = k0 < 16 ? &p.hre : &p.him;
      l.b0 = (k0 & 15) * 64; l.b1 = idx * 256 + swap * 128; l.db0 = 64; l.db1 = 0; l.c0 = l.c1 = 0; l.e1 = 128 - swap * 256;
    } else {
      l.mb0 = l.mb1 = &p.wd;
      l.b0 = 0; l.b1 = (k0 - 32) * 64; l.db0 = 0; l.db1 = 64; l.c0 = idx * 4 + swap * 2; l.c1 = l.c0 ^ 2; l.e1 = 0;
    }
  }
  return l;
}
__device__ __forceinline__ void issue_loads(Loads& l, uint32_t sa, uint32_t fb, bool keep_a) {
  mbar_expect(fb, keep_a ? B_BYTES : ST_BYTES);
  if (!keep_a) tma2d(sa, l.ma, l.a0, l.a1, fb, l.pa);
  tma3d(sa + A_BYTES, l.mb0, l.b0, l.b1, l.c0, fb, l.pb);
  tma3d(sa + A_BYTES + 16384, l.mb1, l.b0, l.b1 + l.e1, l.c1, fb, l.pb);
  l.a0 = (l.a0 + l.da0) & l.wrap; l.a1 += l.da1; l.b0 += l.db0; l.b1 = (l.b1 + l.db1) & l.wrap;
}

template <int KM>
__device__ __forceinline__ void mma_block(float (&d)[128], uint32_t da, uint32_t db, uint32_t acc) {
  constexpr uint32_t LBO = KM ? (1u << 16) : (512u << 16), STEP = KM ? 2 : 128;
  wg_fence();
  wgmma256<1 - KM>(d, da, db + LBO, acc);
  wgmma256<1 - KM>(d, da + 2, db + (LBO + STEP), 1);
  wgmma256<1 - KM>(d, da + 4, db + (LBO + 2 * STEP), 1);
  wgmma256<1 - KM>(d, da + 6, db + (LBO + 3 * STEP), 1);
  wg_commit();
}

#define ADVANCE()                                          \
  const uint32_t ebar = fbar + (B_EMPTY - B_FULL);         \
  asm volatile("" : "+r"(st));                             \
  st = (st + 1) & (STAGES - 1);                            \
  ph ^= (st == 0);                                         \
  fbar = bars + B_FULL + 8 * st;                           \
  da = da0 + st * (ST_BYTES >> 4);                         \
  db = db0 + st * (ST_BYTES >> 4);                         \
  full = mbar_test(fbar, ph);
#define KSTEP(KM, WORK)                                    \
  {                                                        \
    if (!full) mbar_wait(fbar, ph);                        \
    mma_block<KM>(d, da, db, acc);                         \
    acc = 1;                                               \
    WORK;                                                  \
    ADVANCE();                                             \
    wg_wait_all(d);                                        \
    if (lane == 0) mbar_arrive(ebar);                      \
  }
#define SWAIT(buf) mbar_wait(sbar + B_SEMPTY + 8 * (buf), sph ^ 1)
#define SDONE(buf) stage_done(sbar + B_SFULL + 8 * (buf))

__global__ void __cluster_dims__(2, 1, 1) __launch_bounds__(384, 1) fused_kernel(const __grid_constant__ Params p) {
  extern __shared__ uint8_t smem_raw[];
  const uint32_t sbase = (smem_u32(smem_raw) + 1023) & ~1023u;
  const uint32_t bars = sbase + OFF_BAR;
  const int lane = threadIdx.x & 31;
  const int b = blockIdx.x;
  const uint32_t seg0 = p.first[b].x;
  const uint32_t fl = p.first[b].y;
  const CUtensorMap* f_ma = ptr_add(&p.sre, fl & 0x180);
  const CUtensorMap* f_mb0 = ptr_add(&p.sre, (fl >> 2) & 0x380);
  const CUtensorMap* f_mb1 = ptr_add(&p.sre, (fl >> 5) & 0x380);
  const int f_row = (fl >> 8) & 0x780, f_c0 = fl & 63, f_c1 = fl >> 24;
#define FIRST_LOADS(s)                                                          \
  {                                                                             \
    const uint32_t fb = bars + B_FULL + 8 * (s), sa = sbase + (s) * ST_BYTES;   \
    mbar_expect(fb, ST_BYTES);                                                  \
    tma2d(sa, f_ma, (s) * 64, f_row, fb, POL_NORMAL);                           \
    tma3d(sa + A_BYTES, f_mb0, 0, (s) * 64, f_c0, fb, POL_NORMAL);              \
    tma3d(sa + A_BYTES + 16384, f_mb1, 0, (s) * 64, f_c1, fb, POL_NORMAL);      \
  }
  if (elect_one() && threadIdx.x < 32) {
    mbar_init(bars + B_FULL, 1);
    asm volatile("fence.mbarrier_init.release.cluster;" ::: "memory");
    FIRST_LOADS(0)
  }
  const int warp = __shfl_sync(0xffffffff, threadIdx.x >> 5, 0);

  if (warp >= 4) {
    asm volatile("setmaxnreg.inc.sync.aligned.u32 224;");
    const uint32_t w = (warp >> 2) - 1, wq = warp & 3;
    float d[128];
    uint32_t pk[64];
    float s0 = 0.f, s1 = 0.f;
    const uint32_t sbar = bars + w * 16;
    const uint32_t lane_off = (wq * 16 + (lane & 15)) * 128 + (((lane >> 4) ^ (lane & 7)) << 4);
    const uint32_t sa_stg = sbase + OFF_STG + w * 16384 + lane_off;
    const uint32_t da0 = (((sbase + w * 8192) & 0x3FFFF) >> 4) | (1u << 16);
    const uint32_t db0 = ((sbase + A_BYTES) & 0x3FFFF) >> 4;
    uint32_t st = 0, ph = 0, sph = 0, fbar = bars + B_FULL, da = da0, db = db0, acc = 0;
    uint32_t seg = seg0, next = 0;
    int si = 1, left = SEG_NK(seg);
    bool full = false;
    asm volatile("bar.sync 1, 384;" ::: "memory");
    asm volatile("barrier.cluster.arrive.relaxed.aligned;" ::: "memory");

    if (w == 1) {
      mbar_wait(fbar, 0);
      const uint32_t t0 = (uint32_t)clock();
      while ((uint32_t)clock() - t0 < 200u);
    }
    while (true) {
      const int epi = SEG_EPI(seg);
      if (SEG_TYPE(seg) < T_OUTK) {
        for (; left > (epi != E_NONE && epi != E_SEND); left--)
          KSTEP(0,
            if (left <= 4) {
              next = c_sched.s[b][si];
              if (left == 2 && SEG_TYPE(seg) <= T_GU) {
                if (si == 1) { mbar_wait(bars + B_GREADY, 0); asm volatile("barrier.cluster.wait.aligned;" ::: "memory"); }
                const float2* gp = ptr_add(p.sync->gate, (SEG_M(seg) * 128 + w * 64 + wq * 16 + (lane >> 2)) * 8 + (SEG_TYPE(seg) - T_PQ) * 4);
                asm volatile("ld.relaxed.gpu.global.f32 %0, [%1];" : "=f"(s0) : "l"(gp) : "memory");
                asm volatile("ld.relaxed.gpu.global.f32 %0, [%1+64];" : "=f"(s1) : "l"(gp) : "memory");
              }
            })
      } else {
        for (; left > 0; left--) KSTEP(1, next = c_sched.s[b][si])
      }
      const bool neg = SEG_IDX(seg) >= 4;
      const uint32_t lcol = SEG_IDX(seg) * 256, lrow = SEG_M(seg) * 128;
      seg = next;
      si++;
      left = SEG_NK(seg);
      if (epi > E_GU) {
        if (epi == E_SEND) break;
        KSTEP(0, if (epi != E_PQ) s0 = s1 = 1.f; else if (neg) { s0 = -s0; s1 = -s1; })
#pragma unroll
        for (int i = 0; i < 64; i++) pk[i] = pack2(d[2 * i], d[2 * i + 1]);
        acc = 0;
        if (SEG_TYPE(seg) == T_END) {
          const uint32_t q = st + w, fs = sbase + (q & 3) * ST_BYTES;
          mbar_wait(bars + B_EMPTY + 8 * (q & 3), ph ^ (q >> 2) ^ 1);
#pragma unroll
          for (int sb = 0; sb < 4; sb++) {
#pragma unroll
            for (int jj = 0; jj < 4; jj++)
              stsm4((fs + lane_off + sb * 8192) ^ (jj << 5), pk[16 * sb + 4 * jj], pk[16 * sb + 4 * jj + 1],
                    pk[16 * sb + 4 * jj + 2], pk[16 * sb + 4 * jj + 3]);
            fence_async_smem();
            __syncwarp();
            if (lane == 0) tma_store(&p.outm, fs + wq * 2048 + sb * 8192, lcol + sb * 64, lrow + w * 64 + wq * 16);
          }
          SWAIT(0);
          if (lane == 0) { bulk_commit(); bulk_wait(); mbar_arrive(sbar + B_SFULL); }
          break;
        }
        KSTEP(0, SWAIT(0); plain_chunk<0>(pk, s0, s1, sa_stg); SDONE(0))
        KSTEP(0, SWAIT(1); plain_chunk<1>(pk, s0, s1, sa_stg); SDONE(1); sph ^= 1)
        KSTEP(0, next = c_sched.s[b][si])
        KSTEP(0, SWAIT(0); plain_chunk<2>(pk, s0, s1, sa_stg); SDONE(0))
        KSTEP(0, SWAIT(1); plain_chunk<3>(pk, s0, s1, sa_stg); SDONE(1); sph ^= 1)
        left -= 5;
      } else {
        if (epi == E_NONE) continue;
        KSTEP(0, )
#pragma unroll
        for (int i = 0; i < 64; i++) pk[i] = pack2(d[2 * i], d[2 * i + 1]);
        acc = 0;
        KSTEP(0, SWAIT(0); gu_chunk<0>(pk, s0, s1, sa_stg))
        KSTEP(0, gu_chunk<1>(pk, s0, s1, sa_stg))
        KSTEP(0, gu_chunk<2>(pk, s0, s1, sa_stg))
        KSTEP(0, gu_chunk<3>(pk, s0, s1, sa_stg); SDONE(0))
        KSTEP(0, SWAIT(1); gu_chunk<4>(pk, s0, s1, sa_stg))
        KSTEP(0, gu_chunk<5>(pk, s0, s1, sa_stg))
        KSTEP(0, gu_chunk<6>(pk, s0, s1, sa_stg); next = c_sched.s[b][si])
        KSTEP(0, gu_chunk<7>(pk, s0, s1, sa_stg); SDONE(1); sph ^= 1)
        left -= 8;
      }
    }

    if (SEG_TYPE(seg) != T_END) {
#define BETA_BLOCK(QA, RA, QB, RB)                                                                     \
  {                                                                                                    \
    const uint32_t a = da0 + ((st + QA) & 3) * (ST_BYTES >> 4) + RA * 1024;                            \
    const uint32_t bb = db0 + ((st + QB) & 3) * (ST_BYTES >> 4) + ((512u << 16) + RB * 1024 - 1024);   \
    wgmma128(d, a, bb); wgmma128(d, a + 2, bb + 128); wgmma128(d, a + 4, bb + 256); wgmma128(d, a + 6, bb + 384); \
  }
#define BETA_FULL(Q) mbar_wait(bars + B_FULL + 8 * ((st + Q) & 3), ph ^ ((st + Q) >> 2))
      const uint32_t xoff = OFF_STG + w * 16384 + wq * 2048 + lane * 16;
      const uint32_t rcv = sbase + OFF_STG + w * 16384;
      const uint32_t col = SEG_IDX(seg) * 256 + SEG_FLAG(seg) * 128, row = SEG_M(seg) * 128 + w * 64 + wq * 16;
      const bool addto = SEG_EPI(seg) == E_FINRED;
      uint4* gp = ptr_add(p.out, ((row + (lane >> 3)) * DM + col + (lane & 7) * 8) * 2);
      const uint32_t lp = rcv + wq * 2048 + (lane >> 3) * 128 + (((lane & 7) ^ (lane >> 3)) << 4);
      if (!full) mbar_wait(fbar, ph);
      wg_fence();
      BETA_BLOCK(0, 0, 0, 1)
      BETA_FULL(1);
      wg_fence();
      BETA_BLOCK(0, 2, 1, 0)
      wg_commit();
      BETA_FULL(2);
      {
        const uint32_t dst = map_peer(sbase + xoff, (b & 1) ^ 1), dbar = map_peer(bars + B_RECV + 8 * w, (b & 1) ^ 1);
        mbar_wait_cluster(bars + B_PEER, 0);
#pragma unroll
        for (int q = 0; q < 8; q++) {
          const int i = 64 + 8 * q;
          asm volatile("st.async.weak.shared::cluster.mbarrier::complete_tx::bytes.v4.b32 [%0], {%1,%2,%3,%4}, [%5];"
                       ::"r"(dst + (q >> 2) * 8192 + (q & 3) * 512), "r"(pack2(d[i], d[i + 1])), "r"(pack2(d[i + 2], d[i + 3])),
                         "r"(pack2(d[i + 4], d[i + 5])), "r"(pack2(d[i + 6], d[i + 7])), "r"(dbar) : "memory");
        }
      }
      wg_wait_lo(d);
      wg_fence();
      BETA_BLOCK(1, 1, 1, 2)
      BETA_BLOCK(2, 0, 2, 1)
      BETA_FULL(3);
      wg_fence();
      BETA_BLOCK(2, 2, 3, 0)
      wg_commit();
      mbar_wait_cluster(bars + B_RECV + 8 * w, 0);
#pragma unroll
      for (int q = 0; q < 8; q++)
        asm volatile("ld.shared.v4.u32 {%0,%1,%2,%3}, [%4];" : "=r"(pk[4 * q]), "=r"(pk[4 * q + 1]), "=r"(pk[4 * q + 2]), "=r"(pk[4 * q + 3])
                     : "r"(rcv + wq * 2048 + lane * 16 + (q >> 2) * 8192 + (q & 3) * 512) : "memory");
      __syncwarp();
      mbar_wait(bars + B_HOK, 0);
      wg_wait_lo(d);
#pragma unroll
      for (int sb = 0; sb < 2; sb++) {
#pragma unroll
        for (int jj = 0; jj < 4; jj++) {
          uint32_t o[4];
#pragma unroll
          for (int r = 0; r < 4; r++) {
            const int i = 32 * sb + 8 * jj + 2 * r;
            o[r] = pack2(d[i] + bf_lo(pk[i >> 1]), d[i + 1] + bf_hi(pk[i >> 1]));
          }
          stsm4((rcv + lane_off + sb * 8192) ^ (jj << 5), o[0], o[1], o[2], o[3]);
        }
        __syncwarp();
#pragma unroll
        for (int q = 0; q < 4; q++) {
          uint32_t v0, v1, v2, v3;
          asm volatile("ld.shared.v4.u32 {%0,%1,%2,%3}, [%4];" : "=r"(v0), "=r"(v1), "=r"(v2), "=r"(v3)
                       : "r"((lp + sb * 8192 + q * 512) ^ ((q & 1) << 6)) : "memory");
          if (addto)
            asm volatile("red.relaxed.gpu.global.add.noftz.v4.bf16x2 [%0], {%1,%2,%3,%4};"
                         ::"l"(gp + sb * 8 + q * 512), "r"(v0), "r"(v1), "r"(v2), "r"(v3) : "memory");
          else
            asm volatile("st.global.v4.u32 [%0], {%1,%2,%3,%4};" ::"l"(gp + sb * 8 + q * 512), "r"(v0), "r"(v1), "r"(v2), "r"(v3) : "memory");
        }
      }
    }
  } else {
    asm volatile("setmaxnreg.dec.sync.aligned.u32 56;");
    if (warp > 2) {
      unsigned ep = 0;
      asm volatile("bar.sync 1, 384;" ::: "memory");
      asm volatile("barrier.cluster.arrive.relaxed.aligned;" ::: "memory");
      if (lane == 0) {
        asm volatile("ld.relaxed.gpu.global.u32 %0, [%1];" : "=r"(ep) : "l"(&p.sync->epoch[b]) : "memory");
        ep += 1;
        p.sync->epoch[b] = ep;
        asm volatile("st.shared.u32 [%0], %1;" ::"r"(bars + W_EPOCH), "r"(ep) : "memory");
        mbar_arrive(bars + B_EPOCH);
        prefetch_map(&p.xa); prefetch_map(&p.wg); prefetch_map(&p.wu); prefetch_map(&p.zst); prefetch_map(&p.zld);
        prefetch_map(&p.hre); prefetch_map(&p.him); prefetch_map(&p.wd); prefetch_map(&p.outm);
        __nanosleep(3000);
        poll_ge(&p.sync->gatecnt[0], ep * 256);
        mbar_arrive(bars + B_GREADY);
      }
      ep = __shfl_sync(0xffffffff, ep, 0);
      const unsigned target = lane < 2 ? ep * 4 : ep;
      uint32_t ready = 0, cur_m = 99, cnt = 0, published = 0;
      for (int si = 1;; si++) {
        const uint32_t seg = c_sched.s[b][si];
        const uint32_t type = SEG_TYPE(seg), m = SEG_M(seg);
        if (type == T_END) break;
        if (type < T_OUTM) continue;
        if (m != cur_m) { cur_m = m; ready = 0; }
        const unsigned* fp = ptr_add(p.sync->flags, (m * 32 + lane) * 4);
        const uint32_t kend = SEG_K0(seg) + SEG_NK(seg);
        for (uint32_t kb = SEG_K0(seg); kb < kend; kb++) {
          const uint32_t src = kb < 32 ? (kb >> 4) : (kb >> 1) - 14;
          if (!((ready >> src) & 1)) {
            if (cnt != published) {
              published = cnt;
              if (lane == 0) asm volatile("st.release.cta.shared.u32 [%0], %1;" ::"r"(bars + W_CLEAR), "r"(cnt) : "memory");
            }
            uint32_t it = 0;
            while (!((__ballot_sync(0xffffffff, (int)(ld_relaxed(fp) - target) >= 0) >> src) & 1)) {
              __nanosleep(300);
              trap_if(++it > (1u << 22));
            }
            ready = __ballot_sync(0xffffffff, (int)(ld_acquire(fp) - target) >= 0);
            fence_async();
            __syncwarp();
          }
          cnt++;
        }
      }
      if (lane == 0) asm volatile("st.release.cta.shared.u32 [%0], %1;" ::"r"(bars + W_CLEAR), "r"(cnt) : "memory");
    } else if (warp > 0) {
      const uint32_t w = warp - 1;
      const uint32_t stg = sbase + OFF_STG + w * 16384;
      if (warp == 1 && elect_one()) {
#pragma unroll
        for (int s = 0; s < STAGES; s++) mbar_init(bars + B_EMPTY + 8 * s, 8);
#pragma unroll
        for (int s = 0; s < 4; s++) { mbar_init(bars + B_SFULL + 8 * s, 4); mbar_init(bars + B_SEMPTY + 8 * s, 1); }
        mbar_init(bars + B_RECV, 1); mbar_init(bars + B_RECV + 8, 1);
#pragma unroll
        for (int s = 0; s < 10; s++) mbar_init(bars + B_GLOAD + 8 * s, 1);
        asm volatile("st.shared.u32 [%0], %1;" ::"r"(bars + W_CLEAR), "r"(0) : "memory");
        asm volatile("fence.mbarrier_init.release.cluster;" ::: "memory");
        fence_async_smem();
      }
      __syncwarp();
      asm volatile("bar.sync 1, 384;" ::: "memory");
      asm volatile("barrier.cluster.arrive.relaxed.aligned;" ::: "memory");
      if (b < 128) {
        const int row0 = SEG_M(seg0) * 128 + SEG_IDX(seg0) * 16 + w * 8;
        float zrow = 0.f;
        const uint4* wp = ptr_add(p.gw, lane * 16);
        const uint4* xp = p.x + row0 * 128;
        uint4 wv[4];
#pragma unroll
        for (int i = 0; i < 4; i++) wv[i] = __ldg(wp + i * 32);
        mbar_wait(bars + B_FULL + 8, 0);
#define GATE_LOAD(r)                                                                                               \
  if (lane == 0) {                                                                                                 \
    const uint32_t gb = bars + B_GLOAD + 16 * w + 4 * ((r) & 2);                                                   \
    mbar_expect(gb, 4096);                                                                                         \
    asm volatile("cp.async.bulk.shared::cluster.global.mbarrier::complete_tx::bytes [%0], [%1], 4096, [%2];"      \
                 ::"r"(stg + (r) * 2048), "l"(ptr_add(xp, (r) * 2048)), "r"(gb) : "memory");                       \
  }
        GATE_LOAD(0)
#pragma unroll 1
        for (int r = 0; r < 8; r += 2) {
          mbar_wait(bars + B_GLOAD + 16 * w + 4 * (r & 2), (r >> 2) & 1);
          if (r < 6) GATE_LOAD(r + 2)
          float z0 = 0.f, z1 = 0.f, y0 = 0.f, y1 = 0.f;
#pragma unroll
          for (int i = 0; i < 4; i++) {
            uint32_t a[4], c[4];
            asm volatile("ld.shared.v4.u32 {%0,%1,%2,%3}, [%4];" : "=r"(a[0]), "=r"(a[1]), "=r"(a[2]), "=r"(a[3])
                         : "r"(stg + r * 2048 + i * 512 + lane * 16) : "memory");
            asm volatile("ld.shared.v4.u32 {%0,%1,%2,%3}, [%4+2048];" : "=r"(c[0]), "=r"(c[1]), "=r"(c[2]), "=r"(c[3])
                         : "r"(stg + r * 2048 + i * 512 + lane * 16) : "memory");
            const uint32_t wq4[4] = {wv[i].x, wv[i].y, wv[i].z, wv[i].w};
#pragma unroll
            for (int e = 0; e < 4; e++) {
              z0 = fmaf(bf_lo(a[e]), bf_lo(wq4[e]), z0); z1 = fmaf(bf_hi(a[e]), bf_hi(wq4[e]), z1);
              y0 = fmaf(bf_lo(c[e]), bf_lo(wq4[e]), y0); y1 = fmaf(bf_hi(c[e]), bf_hi(wq4[e]), y1);
            }
          }
          float z = z0 + z1, y = y0 + y1;
          const float keep = lane < 16 ? z : y, give = lane < 16 ? y : z;
          z = keep + __shfl_xor_sync(0xffffffff, give, 16);
#pragma unroll
          for (int o = 8; o > 0; o >>= 1) z += __shfl_xor_sync(0xffffffff, z, o);
          if ((lane & 15) == r + (lane >> 4)) zrow = z;
        }
        const float ic = 1.f + ex2f(zrow * 1.4426950408889634f);
        const float g = rcpf(1.f + ex2f(zrow * -1.4426950408889634f));
        if ((lane & 15) < 8 && (lane & 1) == (lane >> 4)) *ptr_add(p.sync->gate, (row0 + (lane & 15)) * 8) = make_float2(g, ic > 1e38f ? 1e38f : ic);
        __syncwarp();
        if (lane == 0) red_release(&p.sync->gatecnt[0]);
      }
      asm volatile("barrier.cluster.wait.aligned;" ::: "memory");
      if (elect_one()) {
        uint32_t ep, fph = 0, mine = w ^ 1, tph = w ^ 1;
        mbar_wait(bars + B_EPOCH, 0);
        asm volatile("ld.shared.u32 %0, [%1];" : "=r"(ep) : "r"(bars + W_EPOCH) : "memory");
        for (int si = 0;; si++) {
          const uint32_t seg = c_sched.s[b][si];
          const uint32_t epi = SEG_EPI(seg), m = SEG_M(seg), idx = SEG_IDX(seg);
          if (SEG_TYPE(seg) == T_END) break;
          if (epi == E_NONE) continue;
          if (epi == E_SEND) {
            if (mine) {
              if (SEG_EPI(c_sched.s[b][si + 1]) == E_FINRED) {
                poll_ge(ptr_add(p.sync->hflag, (m * 4 + idx) * 4), ep);
                fence_async();
              }
              mbar_arrive(bars + B_HOK);
            } else {
              mbar_expect(bars + B_RECV, 16384);
              mbar_expect(bars + B_RECV + 8, 16384);
              mbar_arrive_remote(map_peer(bars + B_PEER, (b & 1) ^ 1));
            }
            break;
          }
          mine ^= 1;
          if (mine) {
            if (epi == E_GU) fph ^= 1;
            continue;
          }
          mbar_wait(bars + B_TURN + 8 * w, tph);
          tph ^= 1;
          if (SEG_TYPE(c_sched.s[b][si + 1]) == T_END) {
            mbar_wait(bars + B_SFULL, fph);
            mbar_wait(bars + B_SFULL + 16, fph);
            red_release(ptr_add(p.sync->flags, (512 + m * 4 + idx) * 4));
            break;
          }
          const uint32_t nsb = epi == E_GU ? 2 : 4;
          uint32_t row, flag;
          if (epi == E_PQ) { row = (m * KZ + idx * 4) * 128; flag = m * 32 + (idx >> 2); }
          else if (epi == E_GU) { row = (m * KZ + 32 + idx * 2) * 128; flag = m * 32 + 2 + idx; }
          else { row = m * 128; flag = 512 + m * 4 + idx; }
#pragma unroll 1
          for (uint32_t sb = 0; sb < nsb; sb++) {
            const uint32_t buf = sb & 1;
#pragma unroll 1
            for (uint32_t g = 0; g < 2; g++) {
              const uint32_t src = sbase + OFF_STG + g * 16384 + buf * 8192;
              mbar_wait(bars + B_SFULL + g * 16 + 8 * buf, fph);
              if (epi == E_HELP) {
#pragma unroll
                for (int q = 0; q < 4; q++) tma_store(&p.outm, src + q * 2048, idx * 256 + sb * 64, row + g * 64 + q * 16);
              } else {
                tma_store(&p.zst, src, 0, row + sb * 128 + g * 64);
              }
            }
            bulk_commit();
            bulk_wait_read();
            mbar_arrive(bars + B_SEMPTY + 8 * buf);
            mbar_arrive(bars + B_SEMPTY + 16 + 8 * buf);
            fph ^= buf;
          }
          mbar_arrive(bars + B_TURN + 8 * (w ^ 1));
          bulk_wait();
          red_release(ptr_add(p.sync->flags, flag * 4));
        }
      }
    } else {
      if (elect_one()) {
#pragma unroll
        for (int s = 1; s < STAGES; s++) mbar_init(bars + B_FULL + 8 * s, 1);
        asm volatile("fence.mbarrier_init.release.cluster;" ::: "memory");
      }
      __syncwarp();
      asm volatile("bar.arrive 1, 384;" ::: "memory");
      if (elect_one()) {
#pragma unroll 1
        for (int s = 1; s < STAGES; s++) {
          FIRST_LOADS(s)
        }
      }
      __syncwarp();
      asm volatile("barrier.cluster.arrive.relaxed.aligned;" ::: "memory");
      asm volatile("barrier.cluster.wait.aligned;" ::: "memory");
      if (elect_one()) {
        uint32_t seg = seg0 + (STAGES << 12) - (STAGES << 19);
        uint32_t st = 0, ph = 0, cnt = 0, cleared = 0;
#define WAIT_CLEARED()                                                                                            \
  {                                                                                                               \
    uint32_t it = 0;                                                                                              \
    while (cleared <= cnt) {                                                                                      \
      asm volatile("ld.acquire.cta.shared.u32 %0, [%1];" : "=r"(cleared) : "r"(bars + W_CLEAR) : "memory");     \
      trap_if(++it > (1u << 26));                                                                                 \
    }                                                                                                             \
    cnt++;                                                                                                        \
  }
        for (int si = 1; SEG_TYPE(seg) != T_END; si++) {
          const uint32_t type = SEG_TYPE(seg);
          int nk = SEG_NK(seg);
          Loads l = seg_loads(p, seg);
          if (type == T_OUTB) {
            for (int q = 3; q < 5; q++)
              asm volatile("cp.async.bulk.prefetch.tensor.3d.L2.global [%0, {%1, %2, %3}];" ::"l"(l.mb0), "r"(0), "r"(l.b1 + q * 64), "r"(l.c0) : "memory");
#pragma unroll 1
            for (int slot = 0; slot < 12; slot += 3) {
              mbar_wait(bars + B_EMPTY + 8 * st, ph);
              const uint32_t fb = bars + B_FULL + 8 * st;
              mbar_expect(fb, slot < 9 ? ST_BYTES : 16384);
#pragma unroll 1
              for (int r = 0; r < 3 && slot + r < 2 * NBETA; r++) {
                const uint32_t dst = sbase + st * ST_BYTES + r * 16384;
                if ((slot + r) & 1) { tma3d(dst, l.mb0, 0, l.b1, l.c0, fb, l.pb); l.b1 += 64; }
                else { WAIT_CLEARED(); tma2d(dst, l.ma, 0, l.a1, fb, l.pa); l.a1 += 128; }
              }
              if (++st == STAGES) { st = 0; ph ^= 1; }
            }
            break;
          }
#pragma unroll 1
          for (; nk > 0; nk--) {
            if (type >= T_OUTM) WAIT_CLEARED();
            mbar_wait(bars + B_EMPTY + 8 * st, ph);
            issue_loads(l, sbase + st * ST_BYTES, bars + B_FULL + 8 * st, type == T_GU && SEG_FLAG(seg) && nk > 16 - STAGES);
            if (++st == STAGES) { st = 0; ph ^= 1; }
          }
          seg = c_sched.s[b][si];
        }
      }
    }
  }
}

struct FbArgs { const __nv_bfloat16 *x, *sre, *sim, *hre, *him, *wg, *wu, *wd, *gw; __nv_bfloat16 *z, *out; };
__global__ void fallback_kernel(FbArgs a, int mode) {
  __shared__ float sa[32][33], sb[32][33], sc[32][33];
  const int tx = threadIdx.x, ty = threadIdx.y, r = blockIdx.y * 32 + ty, c0 = blockIdx.x * 32, c = c0 + tx;
  const int K = mode == 0 ? SEQ : mode == 1 ? DM : KZ * 64;
  float acc = 0.f, acc2 = 0.f;
  for (int k0 = 0; k0 < K; k0 += 32) {
    if (mode == 0) {
      sa[ty][tx] = __bfloat162float((c0 < DM ? a.sre : a.sim)[r * SEQ + k0 + tx]);
      sb[ty][tx] = __bfloat162float(a.x[(k0 + ty) * DM + (c & (DM - 1))]);
    } else if (mode == 1) {
      sa[ty][tx] = __bfloat162float(a.x[r * DM + k0 + tx]);
      sb[ty][tx] = __bfloat162float(a.wg[(k0 + ty) * FF + c]);
      sc[ty][tx] = __bfloat162float(a.wu[(k0 + ty) * FF + c]);
    } else {
      sa[ty][tx] = __bfloat162float(a.z[r * (KZ * 64) + k0 + tx]);
      if (k0 < 2 * DM) sb[tx][ty] = __bfloat162float((k0 < DM ? a.hre : a.him)[(c0 + ty) * DM + (k0 & (DM - 1)) + tx]);
      else sb[ty][tx] = __bfloat162float(a.wd[(k0 - 2 * DM + ty) * DM + c]);
    }
    __syncthreads();
    for (int k = 0; k < 32; k++) {
      acc = fmaf(sa[ty][k], sb[k][tx], acc);
      if (mode == 1) acc2 = fmaf(sa[ty][k], sc[k][tx], acc2);
    }
    __syncthreads();
  }
  if (mode == 2) { a.out[r * DM + c] = __float2bfloat16(acc); return; }
  float z = 0.f;
  for (int k = tx; k < DM; k += 32) z = fmaf(__bfloat162float(a.x[r * DM + k]), __bfloat162float(a.gw[k]), z);
  for (int o = 16; o > 0; o >>= 1) z += __shfl_xor_sync(0xffffffff, z, o);
  if (mode == 0) a.z[r * (KZ * 64) + c] = __float2bfloat16((c0 < DM ? acc : -acc) / (1.f + expf(-z)));
  else a.z[r * (KZ * 64) + 2 * DM + c] = __float2bfloat16(acc2 / (1.f + expf(-acc)) / (1.f + expf(z)));
}

typedef CUresult (*EncodeFn)(CUtensorMap*, CUtensorMapDataType, cuuint32_t, void*, const cuuint64_t*, const cuuint64_t*,
                             const cuuint32_t*, const cuuint32_t*, CUtensorMapInterleave, CUtensorMapSwizzle,
                             CUtensorMapL2promotion, CUtensorMapFloatOOBfill);

constexpr CUtensorMapL2promotion L2PROM = CU_TENSOR_MAP_L2_PROMOTION_L2_128B;

void map2d(EncodeFn enc, CUtensorMap* m, const void* ptr, uint64_t inner, uint64_t outer, uint32_t rows, bool swz) {
  cuuint64_t dims[2] = {inner, outer}, str[1] = {inner * 2};
  cuuint32_t box[2] = {64, rows}, es[2] = {1, 1};
  enc(m, CU_TENSOR_MAP_DATA_TYPE_BFLOAT16, 2, (void*)ptr, dims, str, box, es, CU_TENSOR_MAP_INTERLEAVE_NONE,
      swz ? CU_TENSOR_MAP_SWIZZLE_128B : CU_TENSOR_MAP_SWIZZLE_NONE, L2PROM, CU_TENSOR_MAP_FLOAT_OOB_FILL_NONE);
}
void map3k(EncodeFn enc, CUtensorMap* m, const void* ptr, uint64_t K, uint64_t N) {
  cuuint64_t dims[3] = {K, N, 1}, str[2] = {K * 2, K * N * 2};
  cuuint32_t box[3] = {64, 128, 1}, es[3] = {1, 1, 1};
  enc(m, CU_TENSOR_MAP_DATA_TYPE_BFLOAT16, 3, (void*)ptr, dims, str, box, es, CU_TENSOR_MAP_INTERLEAVE_NONE,
      CU_TENSOR_MAP_SWIZZLE_128B, L2PROM, CU_TENSOR_MAP_FLOAT_OOB_FILL_NONE);
}
void map3d(EncodeFn enc, CUtensorMap* m, const void* ptr, uint64_t N, uint64_t K, uint32_t chunks) {
  cuuint64_t dims[3] = {64, K, N / 64}, str[2] = {N * 2, 128};
  cuuint32_t box[3] = {64, 64, chunks}, es[3] = {1, 1, 1};
  enc(m, CU_TENSOR_MAP_DATA_TYPE_BFLOAT16, 3, (void*)ptr, dims, str, box, es, CU_TENSOR_MAP_INTERLEAVE_NONE,
      CU_TENSOR_MAP_SWIZZLE_128B, L2PROM, CU_TENSOR_MAP_FLOAT_OOB_FILL_NONE);
}

}

extern "C" void kernel_launch(void* const* d_in, const int* in_sizes, int n_in, void* d_out, int out_size) {
  (void)in_sizes; (void)n_in; (void)out_size;
  EncodeFn enc = nullptr;
  cudaDriverEntryPointQueryResult q;
  cudaGetDriverEntryPoint("cuTensorMapEncodeTiled", (void**)&enc, cudaEnableDefault, &q);
  void *z = nullptr, *sy = nullptr;
  cudaGetSymbolAddress(&z, g_Z);
  cudaGetSymbolAddress(&sy, g_sync);
  cudaFuncSetAttribute(fused_kernel, cudaFuncAttributeMaxDynamicSharedMemorySize, SMEM_BYTES);
  cudaLaunchConfig_t cfg = {};
  cfg.gridDim = dim3(NCTA); cfg.blockDim = dim3(384); cfg.dynamicSmemBytes = SMEM_BYTES;
  cudaLaunchAttribute at;
  at.id = cudaLaunchAttributeClusterDimension;
  at.val.clusterDim.x = 2; at.val.clusterDim.y = 1; at.val.clusterDim.z = 1;
  cfg.attrs = &at; cfg.numAttrs = 1;
  int nclusters = 0;
  cudaOccupancyMaxActiveClusters(&nclusters, fused_kernel, &cfg);
  if (nclusters < NCTA / 2 || !enc) {
    typedef const __nv_bfloat16* P;
    const FbArgs a = {(P)d_in[0], (P)d_in[1], (P)d_in[2], (P)d_in[3], (P)d_in[4], (P)d_in[6], (P)d_in[7], (P)d_in[8],
                      (P)d_in[9], (__nv_bfloat16*)z, (__nv_bfloat16*)d_out};
    fallback_kernel<<<dim3(2 * DM / 32, SEQ / 32), dim3(32, 32)>>>(a, 0);
    fallback_kernel<<<dim3(FF / 32, SEQ / 32), dim3(32, 32)>>>(a, 1);
    fallback_kernel<<<dim3(DM / 32, SEQ / 32), dim3(32, 32)>>>(a, 2);
    return;
  }
  Params p;
  map2d(enc, &p.sre, d_in[1], SEQ, SEQ, 128, true);
  map2d(enc, &p.sim, d_in[2], SEQ, SEQ, 128, true);
  map2d(enc, &p.xa, d_in[0], DM, SEQ, 128, true);
  map3d(enc, &p.xb, d_in[0], DM, SEQ, 2);
  map3d(enc, &p.wg, d_in[6], FF, DM, 2);
  map3d(enc, &p.wu, d_in[7], FF, DM, 2);
  map3k(enc, &p.hre, d_in[3], DM, DM);
  map3k(enc, &p.him, d_in[4], DM, DM);
  map3d(enc, &p.wd, d_in[8], DM, FF, 2);
  map2d(enc, &p.zld, z, 64, ZROWS, 128, false);
  map2d(enc, &p.zst, z, 64, ZROWS, 64, false);
  map2d(enc, &p.outm, d_out, DM, SEQ, 16, true);
  p.x = (const uint4*)d_in[0];
  p.gw = (const uint4*)d_in[9];
  p.sync = (Sync*)sy;
  p.out = (uint4*)d_out;
  for (int b = 0; b < 132; b++) {
    const uint32_t sg = first_seg(b), idx = SEG_IDX(sg), pq = b < 128;
    const uint32_t c0 = pq ? (idx & 3) * 4 : idx * 2, c1 = pq ? c0 + 2 : c0;
    p.first[b].x = sg;
    p.first[b].y = c0 | ((pq ? idx >> 2 : 2) << 7) | ((pq ? 3 : 4) << 9) | ((pq ? 3 : 5) << 12) | (SEG_M(sg) << 15) | (c1 << 24);
  }
  fused_kernel<<<NCTA, 384, SMEM_BYTES>>>(p);
}
```

```cpp
#include <cuda_runtime.h>
#include <cuda_bf16.h>
#include <cuda.h>
#include <stdint.h>

namespace {

constexpr int SEQ = 2048, DM = 1024, FF = 3584;
constexpr int KZ = 88;
constexpr int ZROWS = 16 * KZ * 128;
constexpr int NBETA = 5;

constexpr int STAGES = 4;
constexpr int A_BYTES = 128 * 64 * 2, B_BYTES = 256 * 64 * 2, ST_BYTES = A_BYTES + B_BYTES;
constexpr int OFF_STG = STAGES * ST_BYTES;
constexpr int OFF_BAR = OFF_STG + 32768;
constexpr int SMEM_BYTES = OFF_BAR + 256 + 1024;
constexpr int B_FULL = 0, B_EMPTY = 32, B_SFULL = 64, B_SEMPTY = 96, B_RECV = 128, B_GLOAD = 144, B_PEER = 176, B_HOK = 184,
              B_GREADY = 192, B_EPOCH = 200, B_TURN = 208, W_EPOCH = 224, W_CLEAR = 228;

enum { T_END = 0, T_PQ = 1, T_GU = 2, T_OUTM = 3, T_OUTK = 4, T_OUTB = 5 };
enum { E_NONE = 0, E_GU = 1, E_PQ = 2, E_HELP = 3, E_SEND = 4, E_FIN = 5, E_FINRED = 6 };

constexpr uint32_t mkseg(int type, int m, int idx, int k0, int nk, int flag, int epi) {
  return (uint32_t)type | ((uint32_t)m << 3) | ((uint32_t)idx << 7) | ((uint32_t)k0 << 12) | ((uint32_t)nk << 19) |
         ((uint32_t)flag << 27) | ((uint32_t)epi << 28);
}
#define SEG_TYPE(s) ((s) & 7u)
#define SEG_M(s) (((s) >> 3) & 15u)
#define SEG_IDX(s) (((s) >> 7) & 31u)
#define SEG_K0(s) (((s) >> 12) & 127u)
#define SEG_NK(s) (((s) >> 19) & 127u)
#define SEG_FLAG(s) (((s) >> 27) & 1u)
#define SEG_EPI(s) (((s) >> 28) & 7u)

constexpr int NCTA = 132;
constexpr int MAXSEG = 16;
struct Sched { uint32_t s[132][MAXSEG]; };

constexpr int cl_g(int c) { return c < 4 ? 0 : c < 36 ? (c - 4) % 8 : 1 + (c - 36) % 7; }
constexpr int cl_r(int c) { return c < 4 ? 4 + c : c < 36 ? (c - 4) / 8 : 4 + (c - 36) / 7; }
constexpr int cl_pair(int c) { const int t[8] = {0, 2, 1, 1, 3, 0, 3, 2}; return t[cl_g(c)]; }
constexpr int cl_half(int c) { const int t[8] = {0, 0, 0, 1, 0, 1, 1, 1}; return t[cl_g(c)]; }
constexpr uint32_t first_seg(int b) {
  const int g = cl_g(b >> 1), r = cl_r(b >> 1);
  return b < 128 ? mkseg(T_PQ, (b & 1) + 2 * ((g & 6) + (r >> 2)), 4 * (g & 1) + (r & 3), 0, 32, 0, E_PQ)
                 : mkseg(T_GU, (b - 128) * 4, 19, 0, 16, 0, E_GU);
}

constexpr Sched make_sched() {
  Sched t{};
  const int r3[4] = {19, 20, 26, 27};
  for (int b = 0; b < 128; b++) {
    const int pr = cl_pair(b >> 1), h = cl_half(b >> 1), rk = cl_r(b >> 1), r = b & 1;
    int m = r + 2 * (4 * h + (rk >> 1)), c = 0;
    const int j = 2 * pr + (rk & 1);
    t.s[b][c++] = first_seg(b);
    t.s[b][c++] = mkseg(T_GU, m, j < 3 ? j : 18 + j, 0, 16, 0, E_GU);
    t.s[b][c++] = mkseg(T_GU, m, 3 + j, 12, 16, 1, E_GU);
    t.s[b][c++] = mkseg(T_GU, m, 11 + j, 8, 16, 1, E_GU);
    m = (pr & 1) + 2 * (4 * (pr >> 1) + (rk >> 1));
    const int n = 2 * h + (rk & 1);
    if (!r) {
      t.s[b][c++] = mkseg(T_OUTM, m, n, 32, 14, 0, E_NONE);
      t.s[b][c++] = mkseg(T_OUTK, m, n, 0, 16, 0, E_NONE);
      t.s[b][c++] = mkseg(T_OUTK, m, n, 16, 16, 0, E_SEND);
    } else if (n == 0) {
      t.s[b][c++] = mkseg(T_OUTM, m, 1, 74, 9, 0, E_HELP);
      t.s[b][c++] = mkseg(T_OUTM, m, 0, 76, 7, 1, E_NONE);
      t.s[b][c++] = mkseg(T_OUTM, m, 0, 46, 30, 1, E_SEND);
    } else {
      t.s[b][c++] = mkseg(T_GU, m, r3[n], 0, 16, 0, E_GU);
      t.s[b][c++] = mkseg(T_OUTM, m, n, 46, n == 1 || (n == 2 && (m & 3) == 0) ? 28 : 30, 1, E_SEND);
    }
    t.s[b][c++] = mkseg(T_OUTB, m, n, KZ - NBETA, NBETA, r, n == 0 ? E_FIN : E_FINRED);
  }
  for (int e = 0; e < 4; e++) {
    int c = 0;
    for (int q = 0; q < 4; q++) t.s[128 + e][c++] = mkseg(T_GU, 4 * e + q, r3[0], 0, 16, 0, E_GU);
    for (int q = 0; q < 8; q++) t.s[128 + e][c++] = mkseg(T_OUTM, 4 * e + (q & 3), 2 + (q >> 2), q ? 76 : 74, q ? 7 : 9, 0, E_HELP);
  }
  return t;
}
constexpr bool sched_ok(const Sched& t) {
  int z[16][36] = {}, o[16][8][KZ] = {};
  for (int b = 0; b < NCTA; b++)
    for (int c = 0; SEG_TYPE(t.s[b][c]) != T_END; c++) {
      const uint32_t s = t.s[b][c];
      if (SEG_TYPE(s) <= T_GU) z[SEG_M(s)][SEG_IDX(s) + (SEG_TYPE(s) == T_GU ? 8 : 0)]++;
      else
        for (uint32_t k = SEG_K0(s); k < SEG_K0(s) + SEG_NK(s); k++)
          for (uint32_t hf = 0; hf < 2; hf++)
            if (SEG_TYPE(s) != T_OUTB || hf == SEG_FLAG(s)) o[SEG_M(s)][SEG_IDX(s) * 2 + hf][k]++;
    }
  for (int m = 0; m < 16; m++) {
    for (int i = 0; i < 36; i++) if (z[m][i] != 1) return false;
    for (int i = 0; i < 8; i++) for (int k = 0; k < KZ; k++) if (o[m][i][k] != 1) return false;
  }
  return true;
}
static_assert(sched_ok(make_sched()), "schedule does not cover the problem");
__constant__ Sched c_sched = make_sched();

struct Sync {
  float2 gate[SEQ];
  unsigned flags[16 * 32];
  unsigned hflag[128];
  unsigned epoch[160];
  unsigned gatecnt[32];
};
struct Params {
  const uint4* x;
  const uint4* gw;
  Sync* sync;
  uint4* out;
  uint2 first[132];
  CUtensorMap sre, sim, xa, xb, wg, wu, hre, him, wd, zld, zst, outm;
};

__device__ __align__(1024) __nv_bfloat16 g_Z[(size_t)ZROWS * 64];
__device__ __align__(128) Sync g_sync;

__device__ __forceinline__ uint32_t smem_u32(const void* p) { return (uint32_t)__cvta_generic_to_shared(p); }
__device__ __forceinline__ void mbar_init(uint32_t a, uint32_t c) {
  asm volatile("mbarrier.init.shared::cta.b64 [%0], %1;" ::"r"(a), "r"(c) : "memory");
}
__device__ __forceinline__ void mbar_expect(uint32_t a, uint32_t bytes) {
  asm volatile("mbarrier.arrive.expect_tx.shared::cta.b64 _, [%0], %1;" ::"r"(a), "r"(bytes) : "memory");
}
__device__ __forceinline__ void mbar_arrive(uint32_t a) {
  asm volatile("mbarrier.arrive.shared::cta.b64 _, [%0];" ::"r"(a) : "memory");
}
__device__ __forceinline__ void mbar_wait(uint32_t a, uint32_t parity) {
  asm volatile(
      "{ .reg .pred p; .reg .u32 it;\n"
      "mov.u32 it, 0;\n"
      "WAIT_LOOP:\n"
      "mbarrier.try_wait.parity.shared::cta.b64 p, [%0], %1;\n"
      "@p bra WAIT_DONE;\n"
      "add.u32 it, it, 1;\n"
      "setp.lt.u32 p, it, 0x100000;\n"
      "@p bra WAIT_LOOP;\n"
      "trap;\n"
      "WAIT_DONE:\n"
      "}" ::"r"(a), "r"(parity) : "memory");
}
__device__ __forceinline__ void mbar_wait_cluster(uint32_t a, uint32_t parity) {
  asm volatile(
      "{ .reg .pred p; .reg .u32 it;\n"
      "mov.u32 it, 0;\n"
      "WAIT_LOOP:\n"
      "mbarrier.try_wait.parity.relaxed.cluster.shared::cta.b64 p, [%0], %1;\n"
      "@p bra WAIT_DONE;\n"
      "add.u32 it, it, 1;\n"
      "setp.lt.u32 p, it, 0x100000;\n"
      "@p bra WAIT_LOOP;\n"
      "trap;\n"
      "WAIT_DONE:\n"
      "fence.acquire.sync_restrict::shared::cluster.cluster;\n"
      "}" ::"r"(a), "r"(parity) : "memory");
}
__device__ __forceinline__ bool mbar_test(uint32_t a, uint32_t parity) {
  uint32_t ok;
  asm volatile("{ .reg .pred p; mbarrier.test_wait.parity.shared::cta.b64 p, [%1], %2; selp.u32 %0, 1, 0, p; }"
               : "=r"(ok) : "r"(a), "r"(parity) : "memory");
  return ok;
}
__device__ __forceinline__ void trap_if(bool c) {
  asm volatile("{ .reg .pred p; setp.ne.u32 p, %0, 0; @p trap; }" ::"r"((uint32_t)c));
}
template <typename T>
__device__ __forceinline__ T* ptr_add(T* base, uint32_t bytes) {
  uint64_t r;
  asm("{ .reg .u32 lo, hi; mov.b64 {lo, hi}, %1; add.cc.u32 lo, lo, %2; addc.u32 hi, hi, 0; mov.b64 %0, {lo, hi}; }"
      : "=l"(r) : "l"(base), "r"(bytes));
  return (T*)r;
}
__device__ __forceinline__ unsigned ld_acquire(const unsigned* p) {
  unsigned v;
  asm volatile("ld.acquire.gpu.global.u32 %0, [%1];" : "=r"(v) : "l"(p) : "memory");
  return v;
}
__device__ __forceinline__ unsigned ld_relaxed(const unsigned* p) {
  unsigned v;
  asm volatile("ld.relaxed.gpu.global.u32 %0, [%1];" : "=r"(v) : "l"(p) : "memory");
  return v;
}
__device__ __forceinline__ void red_release(unsigned* p) {
  asm volatile("red.release.gpu.global.add.u32 [%0], 1;" ::"l"(p) : "memory");
}
__device__ __forceinline__ void poll_ge(const unsigned* p, unsigned target) {
  uint32_t it = 0;
  while ((int)(ld_relaxed(p) - target) < 0) {
    __nanosleep(40);
    trap_if(++it > (1u << 22));
  }
  (void)ld_acquire(p);
}
__device__ __forceinline__ void fence_async() { asm volatile("fence.proxy.async.global;" ::: "memory"); }
__device__ __forceinline__ void fence_async_smem() { asm volatile("fence.proxy.async.shared::cta;" ::: "memory"); }
__device__ __forceinline__ void tma2d(uint32_t dst, const CUtensorMap* m, int c0, int c1, uint32_t bar, bool stream) {
  if (stream)
    asm volatile("{ .reg .b64 pol; createpolicy.fractional.L2::evict_first.b64 pol, 1.0;\n"
                 "cp.async.bulk.tensor.2d.shared::cluster.global.mbarrier::complete_tx::bytes.L2::cache_hint [%0], [%1, {%3, %4}], [%2], pol; }"
                 ::"r"(dst), "l"(m), "r"(bar), "r"(c0), "r"(c1) : "memory");
  else
    asm volatile("cp.async.bulk.tensor.2d.shared::cluster.global.mbarrier::complete_tx::bytes [%0], [%1, {%3, %4}], [%2];"
                 ::"r"(dst), "l"(m), "r"(bar), "r"(c0), "r"(c1) : "memory");
}
__device__ __forceinline__ void tma3d(uint32_t dst, const CUtensorMap* m, int c0, int c1, int c2, uint32_t bar, bool stream) {
  if (stream)
    asm volatile("{ .reg .b64 pol; createpolicy.fractional.L2::evict_first.b64 pol, 1.0;\n"
                 "cp.async.bulk.tensor.3d.shared::cluster.global.mbarrier::complete_tx::bytes.L2::cache_hint [%0], [%1, {%3, %4, %5}], [%2], pol; }"
                 ::"r"(dst), "l"(m), "r"(bar), "r"(c0), "r"(c1), "r"(c2) : "memory");
  else
    asm volatile("cp.async.bulk.tensor.3d.shared::cluster.global.mbarrier::complete_tx::bytes [%0], [%1, {%3, %4, %5}], [%2];"
                 ::"r"(dst), "l"(m), "r"(bar), "r"(c0), "r"(c1), "r"(c2) : "memory");
}
__device__ __forceinline__ void tma_store(const CUtensorMap* m, uint32_t src, int c0, int c1) {
  asm volatile("cp.async.bulk.tensor.2d.global.shared::cta.bulk_group [%0, {%2, %3}], [%1];"
               ::"l"(m), "r"(src), "r"(c0), "r"(c1) : "memory");
}
__device__ __forceinline__ uint32_t map_peer(uint32_t a, uint32_t cta) {
  uint32_t r;
  asm("mapa.shared::cluster.u32 %0, %1, %2;" : "=r"(r) : "r"(a), "r"(cta));
  return r;
}
__device__ __forceinline__ void mbar_arrive_remote(uint32_t a) {
  asm volatile("fence.release.sync_restrict::shared::cta.cluster;\n"
               "mbarrier.arrive.relaxed.cluster.shared::cluster.b64 _, [%0];" ::"r"(a) : "memory");
}
__device__ __forceinline__ void bulk_commit() { asm volatile("cp.async.bulk.commit_group;" ::: "memory"); }
__device__ __forceinline__ void bulk_wait_read() { asm volatile("cp.async.bulk.wait_group.read 0;" ::: "memory"); }
__device__ __forceinline__ void bulk_wait() { asm volatile("cp.async.bulk.wait_group 0;" ::: "memory"); }
__device__ __forceinline__ void prefetch_map(const CUtensorMap* m) {
  asm volatile("prefetch.tensormap [%0];" ::"l"(m) : "memory");
}
__device__ __forceinline__ bool elect_one() {
  uint32_t p;
  asm volatile("{ .reg .pred p; elect.sync _|p, 0xffffffff; selp.u32 %0, 1, 0, p; }" : "=r"(p));
  return p;
}
__device__ __forceinline__ void stsm4(uint32_t a, uint32_t r0, uint32_t r1, uint32_t r2, uint32_t r3) {
  asm volatile("stmatrix.sync.aligned.m8n8.x4.shared.b16 [%0], {%1,%2,%3,%4};" ::"r"(a), "r"(r0), "r"(r1), "r"(r2), "r"(r3) : "memory");
}
__device__ __forceinline__ uint32_t pack2(float lo, float hi) {
  uint32_t r;
  asm("cvt.rn.bf16x2.f32 %0, %1, %2;" : "=r"(r) : "f"(hi), "f"(lo));
  return r;
}
__device__ __forceinline__ float bf_lo(uint32_t v) { return __uint_as_float(v << 16); }
__device__ __forceinline__ float bf_hi(uint32_t v) { return __uint_as_float(v & 0xffff0000u); }
__device__ __forceinline__ float round_bf(float v) { return bf_lo(pack2(v, v)); }
__device__ __forceinline__ uint32_t mul2(uint32_t a, uint32_t b) {
  uint32_t r;
  asm("mul.rn.bf16x2 %0, %1, %2;" : "=r"(r) : "r"(a), "r"(b));
  return r;
}
__device__ __forceinline__ float ex2f(float x) { float r; asm("ex2.approx.ftz.f32 %0, %1;" : "=f"(r) : "f"(x)); return r; }
__device__ __forceinline__ float rcpf(float x) { float r; asm("rcp.approx.ftz.f32 %0, %1;" : "=f"(r) : "f"(x)); return r; }

#define R8(d, i) "+f"(d[i]), "+f"(d[i + 1]), "+f"(d[i + 2]), "+f"(d[i + 3]), "+f"(d[i + 4]), "+f"(d[i + 5]), "+f"(d[i + 6]), "+f"(d[i + 7])
#define R64LO(d) R8(d, 0), R8(d, 8), R8(d, 16), R8(d, 24), R8(d, 32), R8(d, 40), R8(d, 48), R8(d, 56)
#define R64HI(d) R8(d, 64), R8(d, 72), R8(d, 80), R8(d, 88), R8(d, 96), R8(d, 104), R8(d, 112), R8(d, 120)
#define S64LO "%0,%1,%2,%3,%4,%5,%6,%7,%8,%9,%10,%11,%12,%13,%14,%15,%16,%17,%18,%19,%20,%21,%22,%23,%24,%25,%26,%27,%28,%29,%30,%31," \
              "%32,%33,%34,%35,%36,%37,%38,%39,%40,%41,%42,%43,%44,%45,%46,%47,%48,%49,%50,%51,%52,%53,%54,%55,%56,%57,%58,%59,%60,%61,%62,%63"
#define S64HI "%64,%65,%66,%67,%68,%69,%70,%71,%72,%73,%74,%75,%76,%77,%78,%79,%80,%81,%82,%83,%84,%85,%86,%87,%88,%89,%90,%91,%92,%93,%94,%95," \
              "%96,%97,%98,%99,%100,%101,%102,%103,%104,%105,%106,%107,%108,%109,%110,%111,%112,%113,%114,%115,%116,%117,%118,%119,%120,%121,%122,%123,%124,%125,%126,%127"

constexpr uint32_t DESC_HI = 0x40000040u;
__device__ __forceinline__ uint64_t mkdesc(uint32_t lo) { return ((uint64_t)DESC_HI << 32) | lo; }

template <int TB>
__device__ __forceinline__ void wgmma256(float (&d)[128], uint32_t da, uint32_t db, uint32_t acc) {
  asm volatile("{ .reg .pred p; setp.ne.b32 p, %130, 0;\n"
               "wgmma.mma_async.sync.aligned.m64n256k16.f32.bf16.bf16 {" S64LO "," S64HI "}, %128, %129, p, 1, 1, 0, %131; }"
               : R64LO(d), R64HI(d) : "l"(mkdesc(da)), "l"(mkdesc(db)), "r"(acc), "n"(TB));
}
__device__ __forceinline__ void wgmma128(float (&d)[128], uint32_t da, uint32_t db) {
  asm volatile("wgmma.mma_async.sync.aligned.m64n128k16.f32.bf16.bf16 {" S64LO "}, %64, %65, 1, 1, 1, 0, 1;"
               : R64LO(d) : "l"(mkdesc(da)), "l"(mkdesc(db)));
}
__device__ __forceinline__ void wg_fence() { asm volatile("wgmma.fence.sync.aligned;" ::: "memory"); }
__device__ __forceinline__ void wg_commit() { asm volatile("wgmma.commit_group.sync.aligned;" ::: "memory"); }
__device__ __forceinline__ void wg_wait_all(float (&d)[128]) {
  asm volatile("wgmma.wait_group.sync.aligned 0;" : R64LO(d), R64HI(d)::"memory");
}
__device__ __forceinline__ void wg_wait_lo(float (&d)[128]) {
  asm volatile("wgmma.wait_group.sync.aligned 0;" : R64LO(d)::"memory");
}

__device__ __forceinline__ void stage_done(uint32_t bar) {
  fence_async_smem();
  __syncwarp();
  if (elect_one()) mbar_arrive(bar);
}

template <int C>
__device__ __forceinline__ void gu_chunk(uint32_t (&pk)[64], float ic0, float ic1, uint32_t sa) {
  uint32_t o[4];
#pragma unroll
  for (int r = 0; r < 4; r++) {
    asm volatile("" : "+r"(pk[4 * C + r]), "+r"(pk[32 + 4 * C + r]));
    const uint32_t G = pk[4 * C + r], U = pk[32 + 4 * C + r];
    const float ic = (r & 1) ? ic1 : ic0;
    const float e0 = ex2f(bf_lo(G) * -1.4426950408889634f), e1 = ex2f(bf_hi(G) * -1.4426950408889634f);
    o[r] = pack2(bf_lo(U) * rcpf(fmaf(e0, ic, ic)), bf_hi(U) * rcpf(fmaf(e1, ic, ic)));
  }
  stsm4((sa + (C >> 2) * 8192) ^ ((C & 3) << 5), o[0], o[1], o[2], o[3]);
}
template <int C>
__device__ __forceinline__ void plain_chunk(uint32_t (&pk)[64], uint32_t m0, uint32_t m1, uint32_t sa) {
#pragma unroll
  for (int jj = 0; jj < 4; jj++) {
    uint32_t o[4];
#pragma unroll
    for (int r = 0; r < 4; r++)
      asm volatile("mul.rn.bf16x2 %0, %1, %2;" : "=r"(o[r]) : "r"(pk[16 * C + 4 * jj + r]), "r"((r & 1) ? m1 : m0));
    stsm4((sa + (C & 1) * 8192) ^ (jj << 5), o[0], o[1], o[2], o[3]);
  }
}

struct Loads {
  const CUtensorMap *ma, *mb0, *mb1;
  int a0, a1, da0, da1, b0, b1, db0, db1, c0, c1, e1, wrap;
  bool pa, pb;
};
__device__ __forceinline__ Loads seg_loads(const Params& p, uint32_t seg) {
  const int type = SEG_TYPE(seg), m = SEG_M(seg), idx = SEG_IDX(seg), k0 = SEG_K0(seg), swap = SEG_FLAG(seg);
  Loads l;
  l.pa = type != T_GU;
  l.pb = type != T_PQ;
  l.wrap = type == T_GU ? DM - 1 : -1;
  if (type <= T_GU) {
    l.a0 = k0 * 64; l.a1 = m * 128; l.da0 = 64; l.da1 = 0;
    l.b0 = 0; l.b1 = k0 * 64; l.db0 = 0; l.db1 = 64; l.e1 = 0;
    if (type == T_PQ) { l.ma = idx < 4 ? &p.sre : &p.sim; l.mb0 = l.mb1 = &p.xb; l.c0 = (idx & 3) * 4; l.c1 = l.c0 + 2; }
    else { l.ma = &p.xa; l.mb0 = &p.wg; l.mb1 = &p.wu; l.c0 = l.c1 = idx * 2; }
  } else {
    l.ma = &p.zld; l.a0 = 0; l.a1 = (m * KZ + k0) * 128; l.da0 = 0; l.da1 = 128;
    if (type == T_OUTK) {
      l.mb0 = l.mb1 = k0 < 16 ? &p.hre : &p.him;
      l.b0 = (k0 & 15) * 64; l.b1 = idx * 256 + swap * 128; l.db0 = 64; l.db1 = 0; l.c0 = l.c1 = 0; l.e1 = 128 - swap * 256;
    } else {
      l.mb0 = l.mb1 = &p.wd;
      l.b0 = 0; l.b1 = (k0 - 32) * 64; l.db0 = 0; l.db1 = 64; l.c0 = idx * 4 + swap * 2; l.c1 = l.c0 ^ 2; l.e1 = 0;
    }
  }
  return l;
}
__device__ __forceinline__ void issue_loads(Loads& l, uint32_t sa, uint32_t fb, bool keep_a) {
  mbar_expect(fb, keep_a ? B_BYTES : ST_BYTES);
  if (!keep_a) tma2d(sa, l.ma, l.a0, l.a1, fb, l.pa);
  tma3d(sa + A_BYTES, l.mb0, l.b0, l.b1, l.c0, fb, l.pb);
  tma3d(sa + A_BYTES + 16384, l.mb1, l.b0, l.b1 + l.e1, l.c1, fb, l.pb);
  l.a0 = (l.a0 + l.da0) & l.wrap; l.a1 += l.da1; l.b0 += l.db0; l.b1 = (l.b1 + l.db1) & l.wrap;
}

template <int KM>
__device__ __forceinline__ void mma_block(float (&d)[128], uint32_t da, uint32_t db, uint32_t acc) {
  constexpr uint32_t LBO = KM ? (1u << 16) : (512u << 16), STEP = KM ? 2 : 128;
  wg_fence();
  wgmma256<1 - KM>(d, da, db + LBO, acc);
  wgmma256<1 - KM>(d, da + 2, db + (LBO + STEP), 1);
  wgmma256<1 - KM>(d, da + 4, db + (LBO + 2 * STEP), 1);
  wgmma256<1 - KM>(d, da + 6, db + (LBO + 3 * STEP), 1);
  wg_commit();
}

#define ADVANCE()                                          \
  const uint32_t ebar = fbar + (B_EMPTY - B_FULL);         \
  asm volatile("" : "+r"(st));                             \
  st = (st + 1) & (STAGES - 1);                            \
  ph ^= (st == 0);                                         \
  fbar = bars + B_FULL + 8 * st;                           \
  da = da0 + st * (ST_BYTES >> 4);                         \
  db = db0 + st * (ST_BYTES >> 4);                         \
  full = mbar_test(fbar, ph);
#define KSTEP(KM, WORK)                                    \
  {                                                        \
    if (!full) mbar_wait(fbar, ph);                        \
    mma_block<KM>(d, da, db, acc);                         \
    acc = 1;                                               \
    WORK;                                                  \
    ADVANCE();                                             \
    wg_wait_all(d);                                        \
    if (lane == 0) mbar_arrive(ebar);                      \
  }
#define SWAIT(buf) mbar_wait(sbar + B_SEMPTY + 8 * (buf), sph ^ 1)
#define SDONE(buf) stage_done(sbar + B_SFULL + 8 * (buf))

__global__ void __cluster_dims__(2, 1, 1) __launch_bounds__(384, 1) fused_kernel(const __grid_constant__ Params p) {
  extern __shared__ uint8_t smem_raw[];
  const uint32_t sbase = (smem_u32(smem_raw) + 1023) & ~1023u;
  const uint32_t bars = sbase + OFF_BAR;
  const int lane = threadIdx.x & 31;
  const int b = blockIdx.x;
  const uint32_t seg0 = p.first[b].x;
  const uint32_t fl = p.first[b].y;
  const CUtensorMap* f_ma = ptr_add(&p.sre, fl & 0x180);
  const CUtensorMap* f_mb0 = ptr_add(&p.sre, (fl >> 2) & 0x380);
  const CUtensorMap* f_mb1 = ptr_add(&p.sre, (fl >> 5) & 0x380);
  const int f_row = (fl >> 8) & 0x780, f_c0 = fl & 63, f_c1 = fl >> 24;
#define FIRST_LOADS(s)                                                          \
  {                                                                             \
    const uint32_t fb = bars + B_FULL + 8 * (s), sa = sbase + (s) * ST_BYTES;   \
    mbar_expect(fb, ST_BYTES);                                                  \
    tma2d(sa, f_ma, (s) * 64, f_row, fb, false);                                  \
    tma3d(sa + A_BYTES, f_mb0, 0, (s) * 64, f_c0, fb, false);                     \
    tma3d(sa + A_BYTES + 16384, f_mb1, 0, (s) * 64, f_c1, fb, false);             \
  }
  if (elect_one() && threadIdx.x < 32) {
    mbar_init(bars + B_FULL, 1);
    asm volatile("fence.mbarrier_init.release.cluster;" ::: "memory");
    FIRST_LOADS(0)
  }
  const int warp = __shfl_sync(0xffffffff, threadIdx.x >> 5, 0);

  if (warp >= 4) {
    asm volatile("setmaxnreg.inc.sync.aligned.u32 224;");
    const uint32_t w = (warp >> 2) - 1, wq = warp & 3;
    float d[128];
    uint32_t pk[64];
    float s0 = 0.f, s1 = 0.f;
    const uint32_t sbar = bars + w * 16;
    const uint32_t lane_off = (wq * 16 + (lane & 15)) * 128 + (((lane >> 4) ^ (lane & 7)) << 4);
    const uint32_t sa_stg = sbase + OFF_STG + w * 16384 + lane_off;
    const uint32_t da0 = (((sbase + w * 8192) & 0x3FFFF) >> 4) | (1u << 16);
    const uint32_t db0 = ((sbase + A_BYTES) & 0x3FFFF) >> 4;
    uint32_t st = 0, ph = 0, sph = 0, fbar = bars + B_FULL, da = da0, db = db0, acc = 0;
    uint32_t seg = seg0, next = 0;
    int si = 1, left = SEG_NK(seg);
    bool full = false;
    asm volatile("bar.sync 1, 384;" ::: "memory");
    asm volatile("barrier.cluster.arrive.relaxed.aligned;" ::: "memory");

    if (w == 1) {
      mbar_wait(fbar, 0);
      const uint32_t t0 = (uint32_t)clock();
      while ((uint32_t)clock() - t0 < 200u);
    }
    while (true) {
      const int epi = SEG_EPI(seg);
      if (SEG_TYPE(seg) < T_OUTK) {
        for (; left > (epi != E_NONE && epi != E_SEND); left--)
          KSTEP(0,
            if (left <= 4) {
              next = c_sched.s[b][si];
              if (left == 2 && SEG_TYPE(seg) <= T_GU) {
                if (si == 1) { mbar_wait(bars + B_GREADY, 0); asm volatile("barrier.cluster.wait.aligned;" ::: "memory"); }
                const float2* gp = ptr_add(p.sync->gate, (SEG_M(seg) * 128 + w * 64 + wq * 16 + (lane >> 2)) * 8 + (SEG_TYPE(seg) - T_PQ) * 4);
                asm volatile("ld.relaxed.gpu.global.f32 %0, [%1];" : "=f"(s0) : "l"(gp) : "memory");
                asm volatile("ld.relaxed.gpu.global.f32 %0, [%1+64];" : "=f"(s1) : "l"(gp) : "memory");
              }
            })
      } else {
        for (; left > 0; left--) KSTEP(1, next = c_sched.s[b][si])
      }
      const bool neg = SEG_IDX(seg) >= 4;
      const uint32_t lcol = SEG_IDX(seg) * 256, lrow = SEG_M(seg) * 128;
      seg = next;
      si++;
      left = SEG_NK(seg);
      if (epi > E_GU) {
        if (epi == E_SEND) break;
        uint32_t m0, m1;
        KSTEP(0,
          m0 = epi != E_PQ ? 0x3f803f80u : pack2(s0, s0) ^ (neg ? 0x80008000u : 0u);
          m1 = epi != E_PQ ? 0x3f803f80u : pack2(s1, s1) ^ (neg ? 0x80008000u : 0u))
#pragma unroll
        for (int i = 0; i < 64; i++) pk[i] = pack2(d[2 * i], d[2 * i + 1]);
        acc = 0;
        if (SEG_TYPE(seg) == T_END) {
          const uint32_t q = st + w, fs = sbase + (q & 3) * ST_BYTES;
          mbar_wait(bars + B_EMPTY + 8 * (q & 3), ph ^ (q >> 2) ^ 1);
#pragma unroll
          for (int sb = 0; sb < 4; sb++) {
#pragma unroll
            for (int jj = 0; jj < 4; jj++)
              stsm4((fs + lane_off + sb * 8192) ^ (jj << 5), pk[16 * sb + 4 * jj], pk[16 * sb + 4 * jj + 1],
                    pk[16 * sb + 4 * jj + 2], pk[16 * sb + 4 * jj + 3]);
            fence_async_smem();
            __syncwarp();
            if (lane == 0) tma_store(&p.outm, fs + wq * 2048 + sb * 8192, lcol + sb * 64, lrow + w * 64 + wq * 16);
          }
          SWAIT(0);
          if (lane == 0) { bulk_commit(); bulk_wait(); mbar_arrive(sbar + B_SFULL); }
          break;
        }
        KSTEP(0, SWAIT(0); plain_chunk<0>(pk, m0, m1, sa_stg); SDONE(0))
        KSTEP(0, SWAIT(1); plain_chunk<1>(pk, m0, m1, sa_stg); SDONE(1); sph ^= 1)
        KSTEP(0, next = c_sched.s[b][si])
        KSTEP(0, SWAIT(0); plain_chunk<2>(pk, m0, m1, sa_stg); SDONE(0))
        KSTEP(0, SWAIT(1); plain_chunk<3>(pk, m0, m1, sa_stg); SDONE(1); sph ^= 1)
        left -= 5;
      } else {
        if (epi == E_NONE) continue;
        KSTEP(0, )
#pragma unroll
        for (int i = 0; i < 64; i++) pk[i] = pack2(d[2 * i], d[2 * i + 1]);
        acc = 0;
        KSTEP(0, SWAIT(0); gu_chunk<0>(pk, s0, s1, sa_stg))
        KSTEP(0, gu_chunk<1>(pk, s0, s1, sa_stg))
        KSTEP(0, gu_chunk<2>(pk, s0, s1, sa_stg))
        KSTEP(0, gu_chunk<3>(pk, s0, s1, sa_stg); SDONE(0))
        KSTEP(0, SWAIT(1); gu_chunk<4>(pk, s0, s1, sa_stg))
        KSTEP(0, gu_chunk<5>(pk, s0, s1, sa_stg))
        KSTEP(0, gu_chunk<6>(pk, s0, s1, sa_stg); next = c_sched.s[b][si])
        KSTEP(0, gu_chunk<7>(pk, s0, s1, sa_stg); SDONE(1); sph ^= 1)
        left -= 8;
      }
    }

    if (SEG_TYPE(seg) != T_END) {
#define BETA_BLOCK(QA, RA, QB, RB)                                                                     \
  {                                                                                                    \
    const uint32_t a = da0 + ((st + QA) & 3) * (ST_BYTES >> 4) + RA * 1024;                            \
    const uint32_t bb = db0 + ((st + QB) & 3) * (ST_BYTES >> 4) + ((512u << 16) + RB * 1024 - 1024);   \
    wgmma128(d, a, bb); wgmma128(d, a + 2, bb + 128); wgmma128(d, a + 4, bb + 256); wgmma128(d, a + 6, bb + 384); \
  }
#define BETA_FULL(Q) mbar_wait(bars + B_FULL + 8 * ((st + Q) & 3), ph ^ ((st + Q) >> 2))
      const uint32_t xoff = OFF_STG + w * 16384 + wq * 2048 + lane * 16;
      const uint32_t rcv = sbase + OFF_STG + w * 16384;
      const uint32_t col = SEG_IDX(seg) * 256 + SEG_FLAG(seg) * 128, row = SEG_M(seg) * 128 + w * 64 + wq * 16;
      const bool addto = SEG_EPI(seg) == E_FINRED;
      uint4* gp = ptr_add(p.out, ((row + (lane >> 3)) * DM + col + (lane & 7) * 8) * 2);
      const uint32_t lp = rcv + wq * 2048 + (lane >> 3) * 128 + (((lane & 7) ^ (lane >> 3)) << 4);
      if (!full) mbar_wait(fbar, ph);
      wg_fence();
      BETA_BLOCK(0, 0, 0, 1)
      BETA_FULL(1);
      wg_fence();
      BETA_BLOCK(0, 2, 1, 0)
      wg_commit();
      BETA_FULL(2);
      {
        const uint32_t dst = map_peer(sbase + xoff, (b & 1) ^ 1), dbar = map_peer(bars + B_RECV + 8 * w, (b & 1) ^ 1);
        mbar_wait_cluster(bars + B_PEER, 0);
#pragma unroll
        for (int q = 0; q < 8; q++) {
          const int i = 64 + 8 * q;
          asm volatile("st.async.weak.shared::cluster.mbarrier::complete_tx::bytes.v4.b32 [%0], {%1,%2,%3,%4}, [%5];"
                       ::"r"(dst + (q >> 2) * 8192 + (q & 3) * 512), "r"(pack2(d[i], d[i + 1])), "r"(pack2(d[i + 2], d[i + 3])),
                         "r"(pack2(d[i + 4], d[i + 5])), "r"(pack2(d[i + 6], d[i + 7])), "r"(dbar) : "memory");
        }
      }
      wg_wait_lo(d);
      wg_fence();
      BETA_BLOCK(1, 1, 1, 2)
      BETA_BLOCK(2, 0, 2, 1)
      BETA_FULL(3);
      wg_fence();
      BETA_BLOCK(2, 2, 3, 0)
      wg_commit();
      mbar_wait_cluster(bars + B_RECV + 8 * w, 0);
#pragma unroll
      for (int q = 0; q < 8; q++)
        asm volatile("ld.shared.v4.u32 {%0,%1,%2,%3}, [%4];" : "=r"(pk[4 * q]), "=r"(pk[4 * q + 1]), "=r"(pk[4 * q + 2]), "=r"(pk[4 * q + 3])
                     : "r"(rcv + wq * 2048 + lane * 16 + (q >> 2) * 8192 + (q & 3) * 512) : "memory");
      __syncwarp();
      mbar_wait(bars + B_HOK, 0);
      wg_wait_lo(d);
#pragma unroll
      for (int sb = 0; sb < 2; sb++) {
#pragma unroll
        for (int jj = 0; jj < 4; jj++) {
          uint32_t o[4];
#pragma unroll
          for (int r = 0; r < 4; r++) {
            const int i = 32 * sb + 8 * jj + 2 * r;
            o[r] = pack2(d[i] + bf_lo(pk[i >> 1]), d[i + 1] + bf_hi(pk[i >> 1]));
          }
          stsm4((rcv + lane_off + sb * 8192) ^ (jj << 5), o[0], o[1], o[2], o[3]);
        }
        __syncwarp();
#pragma unroll
        for (int q = 0; q < 4; q++) {
          uint32_t v0, v1, v2, v3;
          asm volatile("ld.shared.v4.u32 {%0,%1,%2,%3}, [%4];" : "=r"(v0), "=r"(v1), "=r"(v2), "=r"(v3)
                       : "r"((lp + sb * 8192 + q * 512) ^ ((q & 1) << 6)) : "memory");
          if (addto)
            asm volatile("red.relaxed.gpu.global.add.noftz.v4.bf16x2 [%0], {%1,%2,%3,%4};"
                         ::"l"(gp + sb * 8 + q * 512), "r"(v0), "r"(v1), "r"(v2), "r"(v3) : "memory");
          else
            asm volatile("st.global.v4.u32 [%0], {%1,%2,%3,%4};" ::"l"(gp + sb * 8 + q * 512), "r"(v0), "r"(v1), "r"(v2), "r"(v3) : "memory");
        }
      }
    }
  } else {
    asm volatile("setmaxnreg.dec.sync.aligned.u32 56;");
    if (warp > 2) {
      unsigned ep = 0;
      asm volatile("bar.sync 1, 384;" ::: "memory");
      asm volatile("barrier.cluster.arrive.relaxed.aligned;" ::: "memory");
      if (lane == 0) {
        asm volatile("ld.relaxed.gpu.global.u32 %0, [%1];" : "=r"(ep) : "l"(&p.sync->epoch[b]) : "memory");
        ep += 1;
        p.sync->epoch[b] = ep;
        asm volatile("st.shared.u32 [%0], %1;" ::"r"(bars + W_EPOCH), "r"(ep) : "memory");
        mbar_arrive(bars + B_EPOCH);
        prefetch_map(&p.xa); prefetch_map(&p.wg); prefetch_map(&p.wu); prefetch_map(&p.zst); prefetch_map(&p.zld);
        prefetch_map(&p.hre); prefetch_map(&p.him); prefetch_map(&p.wd); prefetch_map(&p.outm);
        __nanosleep(3000);
        poll_ge(&p.sync->gatecnt[0], ep * 256);
        mbar_arrive(bars + B_GREADY);
      }
      ep = __shfl_sync(0xffffffff, ep, 0);
      const unsigned target = lane < 2 ? ep * 4 : ep;
      uint32_t ready = 0, cur_m = 99, cnt = 0, published = 0;
      for (int si = 1;; si++) {
        const uint32_t seg = c_sched.s[b][si];
        const uint32_t type = SEG_TYPE(seg), m = SEG_M(seg);
        if (type == T_END) break;
        if (type < T_OUTM) continue;
        if (m != cur_m) { cur_m = m; ready = 0; }
        const unsigned* fp = ptr_add(p.sync->flags, (m * 32 + lane) * 4);
        const uint32_t kend = SEG_K0(seg) + SEG_NK(seg);
        for (uint32_t kb = SEG_K0(seg); kb < kend; kb++) {
          const uint32_t src = kb < 32 ? (kb >> 4) : (kb >> 1) - 14;
          if (!((ready >> src) & 1)) {
            if (cnt != published) {
              published = cnt;
              if (lane == 0) asm volatile("st.release.cta.shared.u32 [%0], %1;" ::"r"(bars + W_CLEAR), "r"(cnt) : "memory");
            }
            uint32_t it = 0;
            while (!((__ballot_sync(0xffffffff, (int)(ld_relaxed(fp) - target) >= 0) >> src) & 1)) {
              __nanosleep(300);
              trap_if(++it > (1u << 22));
            }
            ready = __ballot_sync(0xffffffff, (int)(ld_acquire(fp) - target) >= 0);
            fence_async();
            __syncwarp();
          }
          cnt++;
        }
      }
      if (lane == 0) asm volatile("st.release.cta.shared.u32 [%0], %1;" ::"r"(bars + W_CLEAR), "r"(cnt) : "memory");
    } else if (warp > 0) {
      const uint32_t w = warp - 1;
      const uint32_t stg = sbase + OFF_STG + w * 16384;
      if (warp == 1 && elect_one()) {
#pragma unroll
        for (int s = 0; s < STAGES; s++) mbar_init(bars + B_EMPTY + 8 * s, 8);
#pragma unroll
        for (int s = 0; s < 4; s++) { mbar_init(bars + B_SFULL + 8 * s, 4); mbar_init(bars + B_SEMPTY + 8 * s, 1); }
        mbar_init(bars + B_RECV, 1); mbar_init(bars + B_RECV + 8, 1);
#pragma unroll
        for (int s = 0; s < 10; s++) mbar_init(bars + B_GLOAD + 8 * s, 1);
        asm volatile("st.shared.u32 [%0], %1;" ::"r"(bars + W_CLEAR), "r"(0) : "memory");
        asm volatile("fence.mbarrier_init.release.cluster;" ::: "memory");
        fence_async_smem();
      }
      __syncwarp();
      asm volatile("bar.sync 1, 384;" ::: "memory");
      asm volatile("barrier.cluster.arrive.relaxed.aligned;" ::: "memory");
      if (b < 128) {
        const int row0 = SEG_M(seg0) * 128 + SEG_IDX(seg0) * 16 + w * 8;
        float zrow = 0.f;
        const uint4* wp = ptr_add(p.gw, lane * 16);
        const uint4* xp = p.x + row0 * 128;
        uint4 wv[4];
#pragma unroll
        for (int i = 0; i < 4; i++) wv[i] = __ldg(wp + i * 32);
        mbar_wait(bars + B_FULL + 8, 0);
#define GATE_LOAD(r)                                                                                               \
  if (lane == 0) {                                                                                                 \
    const uint32_t gb = bars + B_GLOAD + 16 * w + 4 * ((r) & 2);                                                   \
    mbar_expect(gb, 4096);                                                                                         \
    asm volatile("cp.async.bulk.shared::cluster.global.mbarrier::complete_tx::bytes [%0], [%1], 4096, [%2];"      \
                 ::"r"(stg + (r) * 2048), "l"(ptr_add(xp, (r) * 2048)), "r"(gb) : "memory");                       \
  }
        GATE_LOAD(0)
#pragma unroll 1
        for (int r = 0; r < 8; r += 2) {
          mbar_wait(bars + B_GLOAD + 16 * w + 4 * (r & 2), (r >> 2) & 1);
          if (r < 6) GATE_LOAD(r + 2)
          float z0 = 0.f, z1 = 0.f, y0 = 0.f, y1 = 0.f;
#pragma unroll
          for (int i = 0; i < 4; i++) {
            uint32_t a[4], c[4];
            asm volatile("ld.shared.v4.u32 {%0,%1,%2,%3}, [%4];" : "=r"(a[0]), "=r"(a[1]), "=r"(a[2]), "=r"(a[3])
                         : "r"(stg + r * 2048 + i * 512 + lane * 16) : "memory");
            asm volatile("ld.shared.v4.u32 {%0,%1,%2,%3}, [%4+2048];" : "=r"(c[0]), "=r"(c[1]), "=r"(c[2]), "=r"(c[3])
                         : "r"(stg + r * 2048 + i * 512 + lane * 16) : "memory");
            const uint32_t wq4[4] = {wv[i].x, wv[i].y, wv[i].z, wv[i].w};
#pragma unroll
            for (int e = 0; e < 4; e++) {
              const uint32_t pa = mul2(a[e], wq4[e]), pc = mul2(c[e], wq4[e]);
              z0 += bf_lo(pa); z1 += bf_hi(pa);
              y0 += bf_lo(pc); y1 += bf_hi(pc);
            }
          }
          float z = z0 + z1, y = y0 + y1;
          const float keep = lane < 16 ? z : y, give = lane < 16 ? y : z;
          z = keep + __shfl_xor_sync(0xffffffff, give, 16);
#pragma unroll
          for (int o = 8; o > 0; o >>= 1) z += __shfl_xor_sync(0xffffffff, z, o);
          if ((lane & 15) == r + (lane >> 4)) zrow = z;
        }
        const float g = round_bf(rcpf(1.f + expf(-round_bf(zrow))));
        const float ic = rcpf(round_bf(1.f - g));
        if ((lane & 15) < 8 && (lane & 1) == (lane >> 4)) *ptr_add(p.sync->gate, (row0 + (lane & 15)) * 8) = make_float2(g, ic > 1e38f ? 1e38f : ic);
        __syncwarp();
        if (lane == 0) red_release(&p.sync->gatecnt[0]);
      }
      asm volatile("barrier.cluster.wait.aligned;" ::: "memory");
      if (elect_one()) {
        uint32_t ep, fph = 0, mine = w ^ 1, tph = w ^ 1;
        mbar_wait(bars + B_EPOCH, 0);
        asm volatile("ld.shared.u32 %0, [%1];" : "=r"(ep) : "r"(bars + W_EPOCH) : "memory");
        for (int si = 0;; si++) {
          const uint32_t seg = c_sched.s[b][si];
          const uint32_t epi = SEG_EPI(seg), m = SEG_M(seg), idx = SEG_IDX(seg);
          if (SEG_TYPE(seg) == T_END) break;
          if (epi == E_NONE) continue;
          if (epi == E_SEND) {
            if (mine) {
              if (SEG_EPI(c_sched.s[b][si + 1]) == E_FINRED) {
                poll_ge(ptr_add(p.sync->hflag, (m * 4 + idx) * 4), ep);
                fence_async();
              }
              mbar_arrive(bars + B_HOK);
            } else {
              mbar_expect(bars + B_RECV, 16384);
              mbar_expect(bars + B_RECV + 8, 16384);
              mbar_arrive_remote(map_peer(bars + B_PEER, (b & 1) ^ 1));
            }
            break;
          }
          mine ^= 1;
          if (mine) {
            if (epi == E_GU) fph ^= 1;
            continue;
          }
          mbar_wait(bars + B_TURN + 8 * w, tph);
          tph ^= 1;
          if (SEG_TYPE(c_sched.s[b][si + 1]) == T_END) {
            mbar_wait(bars + B_SFULL, fph);
            mbar_wait(bars + B_SFULL + 16, fph);
            red_release(ptr_add(p.sync->flags, (512 + m * 4 + idx) * 4));
            break;
          }
          const uint32_t nsb = epi == E_GU ? 2 : 4;
          uint32_t row, flag;
          if (epi == E_PQ) { row = (m * KZ + idx * 4) * 128; flag = m * 32 + (idx >> 2); }
          else if (epi == E_GU) { row = (m * KZ + 32 + idx * 2) * 128; flag = m * 32 + 2 + idx; }
          else { row = m * 128; flag = 512 + m * 4 + idx; }
#pragma unroll 1
          for (uint32_t sb = 0; sb < nsb; sb++) {
            const uint32_t buf = sb & 1;
#pragma unroll 1
            for (uint32_t g = 0; g < 2; g++) {
              const uint32_t src = sbase + OFF_STG + g * 16384 + buf * 8192;
              mbar_wait(bars + B_SFULL + g * 16 + 8 * buf, fph);
              if (epi == E_HELP) {
#pragma unroll
                for (int q = 0; q < 4; q++) tma_store(&p.outm, src + q * 2048, idx * 256 + sb * 64, row + g * 64 + q * 16);
              } else {
                tma_store(&p.zst, src, 0, row + sb * 128 + g * 64);
              }
            }
            bulk_commit();
            bulk_wait_read();
            mbar_arrive(bars + B_SEMPTY + 8 * buf);
            mbar_arrive(bars + B_SEMPTY + 16 + 8 * buf);
            fph ^= buf;
          }
          mbar_arrive(bars + B_TURN + 8 * (w ^ 1));
          bulk_wait();
          red_release(ptr_add(p.sync->flags, flag * 4));
        }
      }
    } else {
      if (elect_one()) {
#pragma unroll
        for (int s = 1; s < STAGES; s++) mbar_init(bars + B_FULL + 8 * s, 1);
        asm volatile("fence.mbarrier_init.release.cluster;" ::: "memory");
      }
      __syncwarp();
      asm volatile("bar.arrive 1, 384;" ::: "memory");
      if (elect_one()) {
#pragma unroll 1
        for (int s = 1; s < STAGES; s++) {
          FIRST_LOADS(s)
        }
      }
      __syncwarp();
      asm volatile("barrier.cluster.arrive.relaxed.aligned;" ::: "memory");
      asm volatile("barrier.cluster.wait.aligned;" ::: "memory");
      if (elect_one()) {
        uint32_t seg = seg0 + (STAGES << 12) - (STAGES << 19);
        uint32_t st = 0, ph = 0, cnt = 0, cleared = 0;
#define WAIT_CLEARED()                                                                                            \
  {                                                                                                               \
    uint32_t it = 0;                                                                                              \
    while (cleared <= cnt) {                                                                                      \
      asm volatile("ld.acquire.cta.shared.u32 %0, [%1];" : "=r"(cleared) : "r"(bars + W_CLEAR) : "memory");     \
      trap_if(++it > (1u << 26));                                                                                 \
    }                                                                                                             \
    cnt++;                                                                                                        \
  }
        for (int si = 1; SEG_TYPE(seg) != T_END; si++) {
          const uint32_t type = SEG_TYPE(seg);
          int nk = SEG_NK(seg);
          Loads l = seg_loads(p, seg);
          if (type == T_OUTB) {
#pragma unroll 1
            for (int slot = 0; slot < 12; slot += 3) {
              mbar_wait(bars + B_EMPTY + 8 * st, ph);
              const uint32_t fb = bars + B_FULL + 8 * st;
              mbar_expect(fb, slot < 9 ? ST_BYTES : 16384);
#pragma unroll 1
              for (int r = 0; r < 3 && slot + r < 2 * NBETA; r++) {
                const uint32_t dst = sbase + st * ST_BYTES + r * 16384;
                if ((slot + r) & 1) { tma3d(dst, l.mb0, 0, l.b1, l.c0, fb, true); l.b1 += 64; }
                else { WAIT_CLEARED(); tma2d(dst, l.ma, 0, l.a1, fb, true); l.a1 += 128; }
              }
              if (++st == STAGES) { st = 0; ph ^= 1; }
            }
            break;
          }
#pragma unroll 1
          for (; nk > 0; nk--) {
            if (type >= T_OUTM) WAIT_CLEARED();
            mbar_wait(bars + B_EMPTY + 8 * st, ph);
            issue_loads(l, sbase + st * ST_BYTES, bars + B_FULL + 8 * st, type == T_GU && SEG_FLAG(seg) && nk > 16 - STAGES);
            if (++st == STAGES) { st = 0; ph ^= 1; }
          }
          seg = c_sched.s[b][si];
        }
      }
    }
  }
}

struct FbArgs { const __nv_bfloat16 *x, *sre, *sim, *hre, *him, *wg, *wu, *wd, *gw; __nv_bfloat16 *z, *out; };
__global__ void fallback_kernel(FbArgs a, int mode) {
  __shared__ float sa[32][33], sb[32][33], sc[32][33];
  const int tx = threadIdx.x, ty = threadIdx.y, r = blockIdx.y * 32 + ty, c0 = blockIdx.x * 32, c = c0 + tx;
  const int K = mode == 0 ? SEQ : mode == 1 ? DM : KZ * 64;
  float acc = 0.f, acc2 = 0.f;
  for (int k0 = 0; k0 < K; k0 += 32) {
    if (mode == 0) {
      sa[ty][tx] = __bfloat162float((c0 < DM ? a.sre : a.sim)[r * SEQ + k0 + tx]);
      sb[ty][tx] = __bfloat162float(a.x[(k0 + ty) * DM + (c & (DM - 1))]);
    } else if (mode == 1) {
      sa[ty][tx] = __bfloat162float(a.x[r * DM + k0 + tx]);
      sb[ty][tx] = __bfloat162float(a.wg[(k0 + ty) * FF + c]);
      sc[ty][tx] = __bfloat162float(a.wu[(k0 + ty) * FF + c]);
    } else {
      sa[ty][tx] = __bfloat162float(a.z[r * (KZ * 64) + k0 + tx]);
      if (k0 < 2 * DM) sb[tx][ty] = __bfloat162float((k0 < DM ? a.hre : a.him)[(c0 + ty) * DM + (k0 & (DM - 1)) + tx]);
      else sb[ty][tx] = __bfloat162float(a.wd[(k0 - 2 * DM + ty) * DM + c]);
    }
    __syncthreads();
    for (int k = 0; k < 32; k++) {
      acc = fmaf(sa[ty][k], sb[k][tx], acc);
      if (mode == 1) acc2 = fmaf(sa[ty][k], sc[k][tx], acc2);
    }
    __syncthreads();
  }
  if (mode == 2) { a.out[r * DM + c] = __float2bfloat16(acc); return; }
  float z = 0.f;
  for (int k = tx; k < DM; k += 32) z += round_bf(__bfloat162float(a.x[r * DM + k]) * __bfloat162float(a.gw[k]));
  for (int o = 16; o > 0; o >>= 1) z += __shfl_xor_sync(0xffffffff, z, o);
  const float g = round_bf(1.f / (1.f + expf(-round_bf(z))));
  if (mode == 0) a.z[r * (KZ * 64) + c] = __float2bfloat16((c0 < DM ? acc : -acc) * g);
  else a.z[r * (KZ * 64) + 2 * DM + c] = __float2bfloat16(acc2 / (1.f + expf(-acc)) * round_bf(1.f - g));
}

typedef CUresult (*EncodeFn)(CUtensorMap*, CUtensorMapDataType, cuuint32_t, void*, const cuuint64_t*, const cuuint64_t*,
                             const cuuint32_t*, const cuuint32_t*, CUtensorMapInterleave, CUtensorMapSwizzle,
                             CUtensorMapL2promotion, CUtensorMapFloatOOBfill);

constexpr CUtensorMapL2promotion L2PROM = CU_TENSOR_MAP_L2_PROMOTION_L2_128B;

void map2d(EncodeFn enc, CUtensorMap* m, const void* ptr, uint64_t inner, uint64_t outer, uint32_t rows, bool swz) {
  cuuint64_t dims[2] = {inner, outer}, str[1] = {inner * 2};
  cuuint32_t box[2] = {64, rows}, es[2] = {1, 1};
  enc(m, CU_TENSOR_MAP_DATA_TYPE_BFLOAT16, 2, (void*)ptr, dims, str, box, es, CU_TENSOR_MAP_INTERLEAVE_NONE,
      swz ? CU_TENSOR_MAP_SWIZZLE_128B : CU_TENSOR_MAP_SWIZZLE_NONE, L2PROM, CU_TENSOR_MAP_FLOAT_OOB_FILL_NONE);
}
void map3k(EncodeFn enc, CUtensorMap* m, const void* ptr, uint64_t K, uint64_t N) {
  cuuint64_t dims[3] = {K, N, 1}, str[2] = {K * 2, K * N * 2};
  cuuint32_t box[3] = {64, 128, 1}, es[3] = {1, 1, 1};
  enc(m, CU_TENSOR_MAP_DATA_TYPE_BFLOAT16, 3, (void*)ptr, dims, str, box, es, CU_TENSOR_MAP_INTERLEAVE_NONE,
      CU_TENSOR_MAP_SWIZZLE_128B, L2PROM, CU_TENSOR_MAP_FLOAT_OOB_FILL_NONE);
}
void map3d(EncodeFn enc, CUtensorMap* m, const void* ptr, uint64_t N, uint64_t K, uint32_t chunks) {
  cuuint64_t dims[3] = {64, K, N / 64}, str[2] = {N * 2, 128};
  cuuint32_t box[3] = {64, 64, chunks}, es[3] = {1, 1, 1};
  enc(m, CU_TENSOR_MAP_DATA_TYPE_BFLOAT16, 3, (void*)ptr, dims, str, box, es, CU_TENSOR_MAP_INTERLEAVE_NONE,
      CU_TENSOR_MAP_SWIZZLE_128B, L2PROM, CU_TENSOR_MAP_FLOAT_OOB_FILL_NONE);
}

}

extern "C" void kernel_launch(void* const* d_in, const int* in_sizes, int n_in, void* d_out, int out_size) {
  (void)in_sizes; (void)n_in; (void)out_size;
  EncodeFn enc = nullptr;
  cudaDriverEntryPointQueryResult q;
  cudaGetDriverEntryPoint("cuTensorMapEncodeTiled", (void**)&enc, cudaEnableDefault, &q);
  void *z = nullptr, *sy = nullptr;
  cudaGetSymbolAddress(&z, g_Z);
  cudaGetSymbolAddress(&sy, g_sync);
  cudaFuncSetAttribute(fused_kernel, cudaFuncAttributeMaxDynamicSharedMemorySize, SMEM_BYTES);
  cudaLaunchConfig_t cfg = {};
  cfg.gridDim = dim3(NCTA); cfg.blockDim = dim3(384); cfg.dynamicSmemBytes = SMEM_BYTES;
  cudaLaunchAttribute at;
  at.id = cudaLaunchAttributeClusterDimension;
  at.val.clusterDim.x = 2; at.val.clusterDim.y = 1; at.val.clusterDim.z = 1;
  cfg.attrs = &at; cfg.numAttrs = 1;
  int nclusters = 0;
  cudaOccupancyMaxActiveClusters(&nclusters, fused_kernel, &cfg);
  if (nclusters < NCTA / 2 || !enc) {
    typedef const __nv_bfloat16* P;
    const FbArgs a = {(P)d_in[0], (P)d_in[1], (P)d_in[2], (P)d_in[3], (P)d_in[4], (P)d_in[6], (P)d_in[7], (P)d_in[8],
                      (P)d_in[9], (__nv_bfloat16*)z, (__nv_bfloat16*)d_out};
    fallback_kernel<<<dim3(2 * DM / 32, SEQ / 32), dim3(32, 32)>>>(a, 0);
    fallback_kernel<<<dim3(FF / 32, SEQ / 32), dim3(32, 32)>>>(a, 1);
    fallback_kernel<<<dim3(DM / 32, SEQ / 32), dim3(32, 32)>>>(a, 2);
    return;
  }
  Params p;
  map2d(enc, &p.sre, d_in[1], SEQ, SEQ, 128, true);
  map2d(enc, &p.sim, d_in[2], SEQ, SEQ, 128, true);
  map2d(enc, &p.xa, d_in[0], DM, SEQ, 128, true);
  map3d(enc, &p.xb, d_in[0], DM, SEQ, 2);
  map3d(enc, &p.wg, d_in[6], FF, DM, 2);
  map3d(enc, &p.wu, d_in[7], FF, DM, 2);
  map3k(enc, &p.hre, d_in[3], DM, DM);
  map3k(enc, &p.him, d_in[4], DM, DM);
  map3d(enc, &p.wd, d_in[8], DM, FF, 2);
  map2d(enc, &p.zld, z, 64, ZROWS, 128, false);
  map2d(enc, &p.zst, z, 64, ZROWS, 64, false);
  map2d(enc, &p.outm, d_out, DM, SEQ, 16, true);
  p.x = (const uint4*)d_in[0];
  p.gw = (const uint4*)d_in[9];
  p.sync = (Sync*)sy;
  p.out = (uint4*)d_out;
  for (int b = 0; b < 132; b++) {
    const uint32_t sg = first_seg(b), idx = SEG_IDX(sg), pq = b < 128;
    const uint32_t c0 = pq ? (idx & 3) * 4 : idx * 2, c1 = pq ? c0 + 2 : c0;
    p.first[b].x = sg;
    p.first[b].y = c0 | ((pq ? idx >> 2 : 2) << 7) | ((pq ? 3 : 4) << 9) | ((pq ? 3 : 5) << 12) | (SEG_M(sg) << 15) | (c1 << 24);
  }
  fused_kernel<<<NCTA, 384, SMEM_BYTES>>>(p);
}
```

```cpp
#include <cuda_runtime.h>
#include <cuda_bf16.h>
#include <cuda.h>
#include <stdint.h>

namespace {

constexpr int SEQ = 2048, DM = 1024, FF = 3584;
constexpr int KZ = 88;
constexpr int ZROWS = 16 * KZ * 128;
constexpr int NBETA = 5;

constexpr int STAGES = 4;
constexpr int A_BYTES = 128 * 64 * 2, B_BYTES = 256 * 64 * 2, ST_BYTES = A_BYTES + B_BYTES;
constexpr int OFF_STG = STAGES * ST_BYTES;
constexpr int OFF_BAR = OFF_STG + 32768;
constexpr int SMEM_BYTES = OFF_BAR + 256 + 1024;
constexpr int B_FULL = 0, B_EMPTY = 32, B_SFULL = 64, B_SEMPTY = 96, B_RECV = 128, B_GLOAD = 144, B_PEER = 176, B_HOK = 184,
              B_GREADY = 192, B_EPOCH = 200, B_TURN = 208, W_EPOCH = 224, W_CLEAR = 228;

enum { T_END = 0, T_PQ = 1, T_GU = 2, T_OUTM = 3, T_OUTK = 4, T_OUTB = 5 };
enum { E_NONE = 0, E_GU = 1, E_PQ = 2, E_HELP = 3, E_SEND = 4, E_FIN = 5, E_FINRED = 6 };

constexpr uint32_t mkseg(int type, int m, int idx, int k0, int nk, int flag, int epi) {
  return (uint32_t)type | ((uint32_t)m << 3) | ((uint32_t)idx << 7) | ((uint32_t)k0 << 12) | ((uint32_t)nk << 19) |
         ((uint32_t)flag << 27) | ((uint32_t)epi << 28);
}
#define SEG_TYPE(s) ((s) & 7u)
#define SEG_M(s) (((s) >> 3) & 15u)
#define SEG_IDX(s) (((s) >> 7) & 31u)
#define SEG_K0(s) (((s) >> 12) & 127u)
#define SEG_NK(s) (((s) >> 19) & 127u)
#define SEG_FLAG(s) (((s) >> 27) & 1u)
#define SEG_EPI(s) (((s) >> 28) & 7u)

constexpr int NCTA = 132;
constexpr int MAXSEG = 16;
struct Sched { uint32_t s[132][MAXSEG]; };

constexpr int cl_g(int c) { return c < 4 ? 0 : c < 36 ? (c - 4) % 8 : 1 + (c - 36) % 7; }
constexpr int cl_r(int c) { return c < 4 ? 4 + c : c < 36 ? (c - 4) / 8 : 4 + (c - 36) / 7; }
constexpr int cl_pair(int c) { const int t[8] = {0, 2, 1, 1, 3, 0, 3, 2}; return t[cl_g(c)]; }
constexpr int cl_half(int c) { const int t[8] = {0, 0, 0, 1, 0, 1, 1, 1}; return t[cl_g(c)]; }
constexpr uint32_t first_seg(int b) {
  const int g = cl_g(b >> 1), r = cl_r(b >> 1);
  return b < 128 ? mkseg(T_PQ, (b & 1) + 2 * ((g & 6) + (r >> 2)), 4 * (g & 1) + (r & 3), 0, 32, 0, E_PQ)
                 : mkseg(T_GU, (b - 128) * 4, 19, 0, 16, 0, E_GU);
}

struct First { int row, c0, c1; uint32_t oa, ob; };
__host__ __device__ constexpr First first_loads(uint32_t b) {
  const uint32_t c = b >> 1, t = c - 36, q = (t * 37) >> 8;
  const uint32_t g = c < 4 ? 0 : c < 36 ? c - 4 : 1 + t - 7 * q, r = c < 4 ? 4 + c : c < 36 ? (c - 4) >> 3 : 4 + q;
  const bool pq = b < 128;
  const int c0 = pq ? (r & 3) * 4 : 38;
  return First{(int)(pq ? ((b & 1) + 2 * ((g & 6) + (r >> 2))) * 128 : (b - 128) * 512), c0, pq ? c0 + 2 : c0,
               pq ? (g & 1) * 128 : 256, pq ? 0u : 128u};
}
constexpr bool first_ok() {
  for (int b = 0; b < NCTA; b++) {
    const First f = first_loads(b);
    const uint32_t s = first_seg(b), idx = SEG_IDX(s);
    if (f.row != (int)SEG_M(s) * 128 || f.c0 != (int)(b < 128 ? (idx & 3) * 4 : idx * 2) || (b < 128 && f.oa != (idx >> 2) * 128)) return false;
  }
  return true;
}
static_assert(first_ok(), "first_loads does not match first_seg");

constexpr Sched make_sched() {
  Sched t{};
  const int r3[4] = {19, 20, 26, 27};
  for (int b = 0; b < 128; b++) {
    const int pr = cl_pair(b >> 1), h = cl_half(b >> 1), rk = cl_r(b >> 1), r = b & 1;
    int m = r + 2 * (4 * h + (rk >> 1)), c = 0;
    const int j = 2 * pr + (rk & 1);
    t.s[b][c++] = first_seg(b);
    t.s[b][c++] = mkseg(T_GU, m, j < 3 ? j : 18 + j, 0, 16, 0, E_GU);
    t.s[b][c++] = mkseg(T_GU, m, 3 + j, 12, 16, 1, E_GU);
    t.s[b][c++] = mkseg(T_GU, m, 11 + j, 8, 16, 1, E_GU);
    m = (pr & 1) + 2 * (4 * (pr >> 1) + (rk >> 1));
    const int n = 2 * h + (rk & 1);
    const bool big = n == 1 || (n == 2 && (m & 3) == 0);
    if (!r) {
      t.s[b][c++] = mkseg(T_OUTM, m, n, 32, 14, 0, E_NONE);
      t.s[b][c++] = mkseg(T_OUTK, m, n, 0, 16, 0, E_NONE);
      t.s[b][c++] = mkseg(T_OUTK, m, n, 16, big ? 15 : 16, 0, E_SEND);
    } else if (n == 0) {
      t.s[b][c++] = mkseg(T_OUTM, m, 1, 74, 9, 0, E_HELP);
      t.s[b][c++] = mkseg(T_OUTM, m, 0, 76, 7, 1, E_NONE);
      t.s[b][c++] = mkseg(T_OUTM, m, 0, 46, 30, 1, E_SEND);
    } else {
      t.s[b][c++] = mkseg(T_GU, m, r3[n], 0, 16, 0, E_GU);
      t.s[b][c++] = mkseg(T_OUTM, m, n, 46, big ? 28 : 30, 1, big ? E_NONE : E_SEND);
      if (big) t.s[b][c++] = mkseg(T_OUTK, m, n, 31, 1, 1, E_SEND);
    }
    t.s[b][c++] = mkseg(T_OUTB, m, n, KZ - NBETA, NBETA, r, n == 0 ? E_FIN : E_FINRED);
  }
  for (int e = 0; e < 4; e++) {
    int c = 0;
    for (int q = 0; q < 4; q++) t.s[128 + e][c++] = mkseg(T_GU, 4 * e + q, r3[0], 0, 16, 0, E_GU);
    for (int q = 0; q < 8; q++) t.s[128 + e][c++] = mkseg(T_OUTM, 4 * e + (q & 3), 2 + (q >> 2), q ? 76 : 74, q ? 7 : 9, 0, E_HELP);
  }
  return t;
}
constexpr bool sched_ok(const Sched& t) {
  int z[16][36] = {}, o[16][8][KZ] = {};
  for (int b = 0; b < NCTA; b++)
    for (int c = 0; SEG_TYPE(t.s[b][c]) != T_END; c++) {
      const uint32_t s = t.s[b][c];
      if (SEG_TYPE(s) <= T_GU) z[SEG_M(s)][SEG_IDX(s) + (SEG_TYPE(s) == T_GU ? 8 : 0)]++;
      else
        for (uint32_t k = SEG_K0(s); k < SEG_K0(s) + SEG_NK(s); k++)
          for (uint32_t hf = 0; hf < 2; hf++)
            if (SEG_TYPE(s) != T_OUTB || hf == SEG_FLAG(s)) o[SEG_M(s)][SEG_IDX(s) * 2 + hf][k]++;
    }
  for (int m = 0; m < 16; m++) {
    for (int i = 0; i < 36; i++) if (z[m][i] != 1) return false;
    for (int i = 0; i < 8; i++) for (int k = 0; k < KZ; k++) if (o[m][i][k] != 1) return false;
  }
  return true;
}
static_assert(sched_ok(make_sched()), "schedule does not cover the problem");
__constant__ Sched c_sched = make_sched();

struct Sync {
  float2 gate[SEQ];
  unsigned flags[16 * 32];
  unsigned hflag[128];
  unsigned epoch[160];
  unsigned gatecnt[32];
};
struct Params {
  const uint4* x;
  const uint4* gw;
  Sync* sync;
  uint4* out;
  uint32_t first[NCTA];
  CUtensorMap sre, sim, xa, xb, wg, wu, hre, him, wd, zld, zst, outm;
};

__device__ __align__(1024) __nv_bfloat16 g_Z[(size_t)ZROWS * 64];
__device__ __align__(128) Sync g_sync;

__device__ __forceinline__ uint32_t smem_u32(const void* p) { return (uint32_t)__cvta_generic_to_shared(p); }
__device__ __forceinline__ void mbar_init(uint32_t a, uint32_t c) {
  asm volatile("mbarrier.init.shared::cta.b64 [%0], %1;" ::"r"(a), "r"(c) : "memory");
}
__device__ __forceinline__ void mbar_expect(uint32_t a, uint32_t bytes) {
  asm volatile("mbarrier.arrive.expect_tx.shared::cta.b64 _, [%0], %1;" ::"r"(a), "r"(bytes) : "memory");
}
__device__ __forceinline__ void mbar_arrive(uint32_t a) {
  asm volatile("mbarrier.arrive.shared::cta.b64 _, [%0];" ::"r"(a) : "memory");
}
__device__ __forceinline__ void mbar_wait(uint32_t a, uint32_t parity) {
  asm volatile(
      "{ .reg .pred p; .reg .u32 it;\n"
      "mov.u32 it, 0;\n"
      "WAIT_LOOP:\n"
      "mbarrier.try_wait.parity.shared::cta.b64 p, [%0], %1;\n"
      "@p bra WAIT_DONE;\n"
      "add.u32 it, it, 1;\n"
      "setp.lt.u32 p, it, 0x100000;\n"
      "@p bra WAIT_LOOP;\n"
      "trap;\n"
      "WAIT_DONE:\n"
      "}" ::"r"(a), "r"(parity) : "memory");
}
__device__ __forceinline__ void mbar_wait_cluster(uint32_t a, uint32_t parity) {
  asm volatile(
      "{ .reg .pred p; .reg .u32 it;\n"
      "mov.u32 it, 0;\n"
      "WAIT_LOOP:\n"
      "mbarrier.try_wait.parity.relaxed.cluster.shared::cta.b64 p, [%0], %1;\n"
      "@p bra WAIT_DONE;\n"
      "add.u32 it, it, 1;\n"
      "setp.lt.u32 p, it, 0x100000;\n"
      "@p bra WAIT_LOOP;\n"
      "trap;\n"
      "WAIT_DONE:\n"
      "fence.acquire.sync_restrict::shared::cluster.cluster;\n"
      "}" ::"r"(a), "r"(parity) : "memory");
}
__device__ __forceinline__ bool mbar_test(uint32_t a, uint32_t parity) {
  uint32_t ok;
  asm volatile("{ .reg .pred p; mbarrier.test_wait.parity.shared::cta.b64 p, [%1], %2; selp.u32 %0, 1, 0, p; }"
               : "=r"(ok) : "r"(a), "r"(parity) : "memory");
  return ok;
}
__device__ __forceinline__ void trap_if(bool c) {
  asm volatile("{ .reg .pred p; setp.ne.u32 p, %0, 0; @p trap; }" ::"r"((uint32_t)c));
}
template <typename T>
__device__ __forceinline__ T* ptr_add(T* base, uint32_t bytes) {
  uint64_t r;
  asm("{ .reg .u32 lo, hi; mov.b64 {lo, hi}, %1; add.cc.u32 lo, lo, %2; addc.u32 hi, hi, 0; mov.b64 %0, {lo, hi}; }"
      : "=l"(r) : "l"(base), "r"(bytes));
  return (T*)r;
}
__device__ __forceinline__ unsigned ld_acquire(const unsigned* p) {
  unsigned v;
  asm volatile("ld.acquire.gpu.global.u32 %0, [%1];" : "=r"(v) : "l"(p) : "memory");
  return v;
}
__device__ __forceinline__ unsigned ld_relaxed(const unsigned* p) {
  unsigned v;
  asm volatile("ld.relaxed.gpu.global.u32 %0, [%1];" : "=r"(v) : "l"(p) : "memory");
  return v;
}
__device__ __forceinline__ void red_release(unsigned* p) {
  asm volatile("red.release.gpu.global.add.u32 [%0], 1;" ::"l"(p) : "memory");
}
__device__ __forceinline__ void poll_ge(const unsigned* p, unsigned target) {
  uint32_t it = 0;
  while ((int)(ld_relaxed(p) - target) < 0) {
    __nanosleep(40);
    trap_if(++it > (1u << 22));
  }
  (void)ld_acquire(p);
}
__device__ __forceinline__ void fence_async() { asm volatile("fence.proxy.async.global;" ::: "memory"); }
__device__ __forceinline__ void fence_async_smem() { asm volatile("fence.proxy.async.shared::cta;" ::: "memory"); }
__device__ __forceinline__ void tma2d(uint32_t dst, const CUtensorMap* m, int c0, int c1, uint32_t bar) {
  asm volatile("cp.async.bulk.tensor.2d.shared::cluster.global.mbarrier::complete_tx::bytes [%0], [%1, {%3, %4}], [%2];"
               ::"r"(dst), "l"(m), "r"(bar), "r"(c0), "r"(c1) : "memory");
}
__device__ __forceinline__ void tma3d(uint32_t dst, const CUtensorMap* m, int c0, int c1, int c2, uint32_t bar) {
  asm volatile("cp.async.bulk.tensor.3d.shared::cluster.global.mbarrier::complete_tx::bytes [%0], [%1, {%3, %4, %5}], [%2];"
               ::"r"(dst), "l"(m), "r"(bar), "r"(c0), "r"(c1), "r"(c2) : "memory");
}
__device__ __forceinline__ void tma_store(const CUtensorMap* m, uint32_t src, int c0, int c1) {
  asm volatile("cp.async.bulk.tensor.2d.global.shared::cta.bulk_group [%0, {%2, %3}], [%1];"
               ::"l"(m), "r"(src), "r"(c0), "r"(c1) : "memory");
}
__device__ __forceinline__ uint32_t map_peer(uint32_t a, uint32_t cta) {
  uint32_t r;
  asm("mapa.shared::cluster.u32 %0, %1, %2;" : "=r"(r) : "r"(a), "r"(cta));
  return r;
}
__device__ __forceinline__ void mbar_arrive_remote(uint32_t a) {
  asm volatile("fence.release.sync_restrict::shared::cta.cluster;\n"
               "mbarrier.arrive.relaxed.cluster.shared::cluster.b64 _, [%0];" ::"r"(a) : "memory");
}
__device__ __forceinline__ void bulk_commit() { asm volatile("cp.async.bulk.commit_group;" ::: "memory"); }
__device__ __forceinline__ void bulk_wait_read() { asm volatile("cp.async.bulk.wait_group.read 0;" ::: "memory"); }
__device__ __forceinline__ void bulk_wait() { asm volatile("cp.async.bulk.wait_group 0;" ::: "memory"); }
__device__ __forceinline__ void prefetch_map(const CUtensorMap* m) {
  asm volatile("prefetch.tensormap [%0];" ::"l"(m) : "memory");
}
__device__ __forceinline__ bool elect_one() {
  uint32_t p;
  asm volatile("{ .reg .pred p; elect.sync _|p, 0xffffffff; selp.u32 %0, 1, 0, p; }" : "=r"(p));
  return p;
}
__device__ __forceinline__ void stsm4(uint32_t a, uint32_t r0, uint32_t r1, uint32_t r2, uint32_t r3) {
  asm volatile("stmatrix.sync.aligned.m8n8.x4.shared.b16 [%0], {%1,%2,%3,%4};" ::"r"(a), "r"(r0), "r"(r1), "r"(r2), "r"(r3) : "memory");
}
__device__ __forceinline__ uint32_t pack2(float lo, float hi) {
  uint32_t r;
  asm("cvt.rn.bf16x2.f32 %0, %1, %2;" : "=r"(r) : "f"(hi), "f"(lo));
  return r;
}
__device__ __forceinline__ float bf_lo(uint32_t v) { return __uint_as_float(v << 16); }
__device__ __forceinline__ float bf_hi(uint32_t v) { return __uint_as_float(v & 0xffff0000u); }
__device__ __forceinline__ float round_bf(float v) { return bf_lo(pack2(v, v)); }
__device__ __forceinline__ uint32_t mul2(uint32_t a, uint32_t b) {
  uint32_t r;
  asm("mul.rn.bf16x2 %0, %1, %2;" : "=r"(r) : "r"(a), "r"(b));
  return r;
}
__device__ __forceinline__ float ex2f(float x) { float r; asm("ex2.approx.ftz.f32 %0, %1;" : "=f"(r) : "f"(x)); return r; }
__device__ __forceinline__ float rcpf(float x) { float r; asm("rcp.approx.ftz.f32 %0, %1;" : "=f"(r) : "f"(x)); return r; }

#define R8(d, i) "+f"(d[i]), "+f"(d[i + 1]), "+f"(d[i + 2]), "+f"(d[i + 3]), "+f"(d[i + 4]), "+f"(d[i + 5]), "+f"(d[i + 6]), "+f"(d[i + 7])
#define R64LO(d) R8(d, 0), R8(d, 8), R8(d, 16), R8(d, 24), R8(d, 32), R8(d, 40), R8(d, 48), R8(d, 56)
#define R64HI(d) R8(d, 64), R8(d, 72), R8(d, 80), R8(d, 88), R8(d, 96), R8(d, 104), R8(d, 112), R8(d, 120)
#define S64LO "%0,%1,%2,%3,%4,%5,%6,%7,%8,%9,%10,%11,%12,%13,%14,%15,%16,%17,%18,%19,%20,%21,%22,%23,%24,%25,%26,%27,%28,%29,%30,%31," \
              "%32,%33,%34,%35,%36,%37,%38,%39,%40,%41,%42,%43,%44,%45,%46,%47,%48,%49,%50,%51,%52,%53,%54,%55,%56,%57,%58,%59,%60,%61,%62,%63"
#define S64HI "%64,%65,%66,%67,%68,%69,%70,%71,%72,%73,%74,%75,%76,%77,%78,%79,%80,%81,%82,%83,%84,%85,%86,%87,%88,%89,%90,%91,%92,%93,%94,%95," \
              "%96,%97,%98,%99,%100,%101,%102,%103,%104,%105,%106,%107,%108,%109,%110,%111,%112,%113,%114,%115,%116,%117,%118,%119,%120,%121,%122,%123,%124,%125,%126,%127"

constexpr uint32_t DESC_HI = 0x40000040u;
__device__ __forceinline__ uint64_t mkdesc(uint32_t lo) { return ((uint64_t)DESC_HI << 32) | lo; }

template <int TB>
__device__ __forceinline__ void wgmma256(float (&d)[128], uint32_t da, uint32_t db, uint32_t acc) {
  asm volatile("{ .reg .pred p; setp.ne.b32 p, %130, 0;\n"
               "wgmma.mma_async.sync.aligned.m64n256k16.f32.bf16.bf16 {" S64LO "," S64HI "}, %128, %129, p, 1, 1, 0, %131; }"
               : R64LO(d), R64HI(d) : "l"(mkdesc(da)), "l"(mkdesc(db)), "r"(acc), "n"(TB));
}
__device__ __forceinline__ void wgmma128(float (&d)[128], uint32_t da, uint32_t db) {
  asm volatile("wgmma.mma_async.sync.aligned.m64n128k16.f32.bf16.bf16 {" S64LO "}, %64, %65, 1, 1, 1, 0, 1;"
               : R64LO(d) : "l"(mkdesc(da)), "l"(mkdesc(db)));
}
__device__ __forceinline__ void wg_fence() { asm volatile("wgmma.fence.sync.aligned;" ::: "memory"); }
__device__ __forceinline__ void wg_commit() { asm volatile("wgmma.commit_group.sync.aligned;" ::: "memory"); }
__device__ __forceinline__ void wg_wait_all(float (&d)[128]) {
  asm volatile("wgmma.wait_group.sync.aligned 0;" : R64LO(d), R64HI(d)::"memory");
}
__device__ __forceinline__ void wg_wait_lo(float (&d)[128]) {
  asm volatile("wgmma.wait_group.sync.aligned 0;" : R64LO(d)::"memory");
}

__device__ __forceinline__ void stage_done(uint32_t bar) {
  fence_async_smem();
  __syncwarp();
  if (elect_one()) mbar_arrive(bar);
}

template <int C>
__device__ __forceinline__ void gu_chunk(uint32_t (&pk)[64], float ic0, float ic1, uint32_t sa) {
  uint32_t o[4];
#pragma unroll
  for (int r = 0; r < 4; r++) {
    asm volatile("" : "+r"(pk[4 * C + r]), "+r"(pk[32 + 4 * C + r]));
    const uint32_t G = pk[4 * C + r], U = pk[32 + 4 * C + r];
    const float ic = (r & 1) ? ic1 : ic0;
    const float e0 = ex2f(bf_lo(G) * -1.4426950408889634f), e1 = ex2f(bf_hi(G) * -1.4426950408889634f);
    o[r] = pack2(bf_lo(U) * rcpf(fmaf(e0, ic, ic)), bf_hi(U) * rcpf(fmaf(e1, ic, ic)));
  }
  stsm4((sa + (C >> 2) * 8192) ^ ((C & 3) << 5), o[0], o[1], o[2], o[3]);
}
template <int C>
__device__ __forceinline__ void plain_chunk(uint32_t (&pk)[64], uint32_t m0, uint32_t m1, uint32_t sa) {
#pragma unroll
  for (int jj = 0; jj < 4; jj++) {
    uint32_t o[4];
#pragma unroll
    for (int r = 0; r < 4; r++)
      asm volatile("mul.rn.bf16x2 %0, %1, %2;" : "=r"(o[r]) : "r"(pk[16 * C + 4 * jj + r]), "r"((r & 1) ? m1 : m0));
    stsm4((sa + (C & 1) * 8192) ^ (jj << 5), o[0], o[1], o[2], o[3]);
  }
}

struct Loads {
  const CUtensorMap *ma, *mb0, *mb1;
  int a0, a1, da0, da1, b0, b1, db0, db1, c0, c1, e1, wrap;
};
__device__ __forceinline__ Loads seg_loads(const Params& p, uint32_t seg) {
  const int type = SEG_TYPE(seg), m = SEG_M(seg), idx = SEG_IDX(seg), k0 = SEG_K0(seg), swap = SEG_FLAG(seg);
  Loads l;
  l.wrap = type == T_GU ? DM - 1 : -1;
  if (type <= T_GU) {
    l.a0 = k0 * 64; l.a1 = m * 128; l.da0 = 64; l.da1 = 0;
    l.b0 = 0; l.b1 = k0 * 64; l.db0 = 0; l.db1 = 64; l.e1 = 0;
    if (type == T_PQ) { l.ma = idx < 4 ? &p.sre : &p.sim; l.mb0 = l.mb1 = &p.xb; l.c0 = (idx & 3) * 4; l.c1 = l.c0 + 2; }
    else { l.ma = &p.xa; l.mb0 = &p.wg; l.mb1 = &p.wu; l.c0 = l.c1 = idx * 2; }
  } else {
    l.ma = &p.zld; l.a0 = 0; l.a1 = (m * KZ + k0) * 128; l.da0 = 0; l.da1 = 128;
    if (type == T_OUTK) {
      l.mb0 = l.mb1 = k0 < 16 ? &p.hre : &p.him;
      l.b0 = (k0 & 15) * 64; l.b1 = idx * 256 + swap * 128; l.db0 = 64; l.db1 = 0; l.c0 = l.c1 = 0; l.e1 = 128 - swap * 256;
    } else {
      l.mb0 = l.mb1 = &p.wd;
      l.b0 = 0; l.b1 = (k0 - 32) * 64; l.db0 = 0; l.db1 = 64; l.c0 = idx * 4 + swap * 2; l.c1 = l.c0 ^ 2; l.e1 = 0;
    }
  }
  return l;
}
__device__ __forceinline__ void issue_loads(Loads& l, uint32_t sa, uint32_t fb, bool keep_a) {
  mbar_expect(fb, keep_a ? B_BYTES : ST_BYTES);
  if (!keep_a) tma2d(sa, l.ma, l.a0, l.a1, fb);
  tma3d(sa + A_BYTES, l.mb0, l.b0, l.b1, l.c0, fb);
  tma3d(sa + A_BYTES + 16384, l.mb1, l.b0, l.b1 + l.e1, l.c1, fb);
  l.a0 = (l.a0 + l.da0) & l.wrap; l.a1 += l.da1; l.b0 += l.db0; l.b1 = (l.b1 + l.db1) & l.wrap;
}

template <int KM>
__device__ __forceinline__ void mma_block(float (&d)[128], uint32_t da, uint32_t db, uint32_t acc) {
  constexpr uint32_t LBO = KM ? (1u << 16) : (512u << 16), STEP = KM ? 2 : 128;
  wg_fence();
  wgmma256<1 - KM>(d, da, db + LBO, acc);
  wgmma256<1 - KM>(d, da + 2, db + (LBO + STEP), 1);
  wgmma256<1 - KM>(d, da + 4, db + (LBO + 2 * STEP), 1);
  wgmma256<1 - KM>(d, da + 6, db + (LBO + 3 * STEP), 1);
  wg_commit();
}

#define ADVANCE()                                          \
  const uint32_t ebar = fbar + (B_EMPTY - B_FULL);         \
  asm volatile("" : "+r"(st));                             \
  st = (st + 1) & (STAGES - 1);                            \
  ph ^= (st == 0);                                         \
  fbar = bars + B_FULL + 8 * st;                           \
  da = da0 + st * (ST_BYTES >> 4);                         \
  db = db0 + st * (ST_BYTES >> 4);                         \
  full = mbar_test(fbar, ph);
#define KSTEP(KM, WORK)                                    \
  {                                                        \
    if (!full) mbar_wait(fbar, ph);                        \
    mma_block<KM>(d, da, db, acc);                         \
    acc = 1;                                               \
    WORK;                                                  \
    ADVANCE();                                             \
    wg_wait_all(d);                                        \
    if (lane == 0) mbar_arrive(ebar);                      \
  }
#define SWAIT(buf) mbar_wait(sbar + B_SEMPTY + 8 * (buf), sph ^ 1)
#define SDONE(buf) stage_done(sbar + B_SFULL + 8 * (buf))

__global__ void __cluster_dims__(2, 1, 1) __launch_bounds__(384, 1) fused_kernel(const __grid_constant__ Params p) {
  extern __shared__ uint8_t smem_raw[];
  const uint32_t sbase = (smem_u32(smem_raw) + 1023) & ~1023u;
  const uint32_t bars = sbase + OFF_BAR;
  const int lane = threadIdx.x & 31;
  int b = blockIdx.x;
#define FIRST_LOADS(s)                                                                    \
  {                                                                                       \
    const uint32_t fb = bars + B_FULL + 8 * (s), sa = sbase + (s) * ST_BYTES;             \
    mbar_expect(fb, ST_BYTES);                                                            \
    tma2d(sa, ptr_add(&p.sre, f.oa), (s) * 64, f.row, fb);                                \
    tma3d(sa + A_BYTES, ptr_add(&p.xb, f.ob), 0, (s) * 64, f.c0, fb);                     \
    tma3d(sa + A_BYTES + 16384, ptr_add(&p.xb, 2 * f.ob), 0, (s) * 64, f.c1, fb);         \
  }
  if (threadIdx.x >= 32) {
    if (threadIdx.x == 32) { prefetch_map(&p.xb); prefetch_map(&p.sre); prefetch_map(&p.sim); }
  } else if (elect_one()) {
    const First f = first_loads(b);
    mbar_init(bars + B_FULL, 1);
    asm volatile("fence.mbarrier_init.release.cluster;" ::: "memory");
    FIRST_LOADS(0)
  }
  asm volatile("" : "+r"(b)::"memory");
  const uint32_t seg0 = p.first[b];
  const int warp = __shfl_sync(0xffffffff, threadIdx.x >> 5, 0);

  if (warp >= 4) {
    asm volatile("setmaxnreg.inc.sync.aligned.u32 224;");
    const uint32_t w = (warp >> 2) - 1, wq = warp & 3;
    float d[128];
    uint32_t pk[64];
    float s0 = 0.f, s1 = 0.f;
    const uint32_t sbar = bars + w * 16;
    const uint32_t lane_off = (wq * 16 + (lane & 15)) * 128 + (((lane >> 4) ^ (lane & 7)) << 4);
    const uint32_t sa_stg = sbase + OFF_STG + w * 16384 + lane_off;
    const uint32_t da0 = (((sbase + w * 8192) & 0x3FFFF) >> 4) | (1u << 16);
    const uint32_t db0 = ((sbase + A_BYTES) & 0x3FFFF) >> 4;
    uint32_t st = 0, ph = 0, sph = 0, fbar = bars + B_FULL, da = da0, db = db0, acc = 0;
    uint32_t seg = seg0, next = 0;
    int si = 1, left = SEG_NK(seg);
    bool full = false;
    asm volatile("barrier.sync 1, 384;" ::: "memory");
    asm volatile("barrier.cluster.arrive.relaxed.aligned;" ::: "memory");

    if (w == 1) {
      mbar_wait(fbar, 0);
      const uint32_t t0 = (uint32_t)clock();
      while ((uint32_t)clock() - t0 < 200u);
    }
    while (true) {
      const int epi = SEG_EPI(seg);
      if (SEG_TYPE(seg) < T_OUTK) {
        for (; left > (epi != E_NONE && epi != E_SEND); left--)
          KSTEP(0,
            if (left <= 4) {
              next = c_sched.s[b][si];
              if (left == 2 && SEG_TYPE(seg) <= T_GU) {
                if (si == 1) { mbar_wait(bars + B_GREADY, 0); asm volatile("barrier.cluster.wait.aligned;" ::: "memory"); }
                const float2* gp = ptr_add(p.sync->gate, (SEG_M(seg) * 128 + w * 64 + wq * 16 + (lane >> 2)) * 8 + (SEG_TYPE(seg) - T_PQ) * 4);
                asm volatile("ld.relaxed.gpu.global.f32 %0, [%1];" : "=f"(s0) : "l"(gp) : "memory");
                asm volatile("ld.relaxed.gpu.global.f32 %0, [%1+64];" : "=f"(s1) : "l"(gp) : "memory");
              }
            })
      } else {
        for (; left > 0; left--) KSTEP(1, next = c_sched.s[b][si])
      }
      const bool neg = SEG_IDX(seg) >= 4;
      const uint32_t lcol = SEG_IDX(seg) * 256, lrow = SEG_M(seg) * 128;
      seg = next;
      si++;
      left = SEG_NK(seg);
      if (epi > E_GU) {
        if (epi == E_SEND) break;
        uint32_t m0, m1;
        KSTEP(0,
          m0 = epi != E_PQ ? 0x3f803f80u : pack2(s0, s0) ^ (neg ? 0x80008000u : 0u);
          m1 = epi != E_PQ ? 0x3f803f80u : pack2(s1, s1) ^ (neg ? 0x80008000u : 0u))
#pragma unroll
        for (int i = 0; i < 64; i++) pk[i] = pack2(d[2 * i], d[2 * i + 1]);
        acc = 0;
        if (SEG_TYPE(seg) == T_END) {
          const uint32_t q = st + w, fs = sbase + (q & 3) * ST_BYTES;
          mbar_wait(bars + B_EMPTY + 8 * (q & 3), ph ^ (q >> 2) ^ 1);
#pragma unroll
          for (int sb = 0; sb < 4; sb++) {
#pragma unroll
            for (int jj = 0; jj < 4; jj++)
              stsm4((fs + lane_off + sb * 8192) ^ (jj << 5), pk[16 * sb + 4 * jj], pk[16 * sb + 4 * jj + 1],
                    pk[16 * sb + 4 * jj + 2], pk[16 * sb + 4 * jj + 3]);
            fence_async_smem();
            __syncwarp();
            if (lane == 0) tma_store(&p.outm, fs + wq * 2048 + sb * 8192, lcol + sb * 64, lrow + w * 64 + wq * 16);
          }
          SWAIT(0);
          if (lane == 0) { bulk_commit(); bulk_wait(); mbar_arrive(sbar + B_SFULL); }
          break;
        }
        KSTEP(0, SWAIT(0); plain_chunk<0>(pk, m0, m1, sa_stg); SDONE(0))
        KSTEP(0, SWAIT(1); plain_chunk<1>(pk, m0, m1, sa_stg); SDONE(1); sph ^= 1)
        KSTEP(0, next = c_sched.s[b][si])
        KSTEP(0, SWAIT(0); plain_chunk<2>(pk, m0, m1, sa_stg); SDONE(0))
        KSTEP(0, SWAIT(1); plain_chunk<3>(pk, m0, m1, sa_stg); SDONE(1); sph ^= 1)
        left -= 5;
      } else {
        if (epi == E_NONE) continue;
        KSTEP(0, )
#pragma unroll
        for (int i = 0; i < 64; i++) pk[i] = pack2(d[2 * i], d[2 * i + 1]);
        acc = 0;
        KSTEP(0, SWAIT(0); gu_chunk<0>(pk, s0, s1, sa_stg))
        KSTEP(0, gu_chunk<1>(pk, s0, s1, sa_stg))
        KSTEP(0, gu_chunk<2>(pk, s0, s1, sa_stg))
        KSTEP(0, gu_chunk<3>(pk, s0, s1, sa_stg); SDONE(0))
        KSTEP(0, SWAIT(1); gu_chunk<4>(pk, s0, s1, sa_stg))
        KSTEP(0, gu_chunk<5>(pk, s0, s1, sa_stg))
        KSTEP(0, gu_chunk<6>(pk, s0, s1, sa_stg); next = c_sched.s[b][si])
        KSTEP(0, gu_chunk<7>(pk, s0, s1, sa_stg); SDONE(1); sph ^= 1)
        left -= 8;
      }
    }

    if (SEG_TYPE(seg) != T_END) {
#define BETA_BLOCK(QA, RA, QB, RB)                                                                     \
  {                                                                                                    \
    const uint32_t a = da0 + ((st + QA) & 3) * (ST_BYTES >> 4) + RA * 1024;                            \
    const uint32_t bb = db0 + ((st + QB) & 3) * (ST_BYTES >> 4) + ((512u << 16) + RB * 1024 - 1024);   \
    wgmma128(d, a, bb); wgmma128(d, a + 2, bb + 128); wgmma128(d, a + 4, bb + 256); wgmma128(d, a + 6, bb + 384); \
  }
#define BETA_FULL(Q) mbar_wait(bars + B_FULL + 8 * ((st + Q) & 3), ph ^ ((st + Q) >> 2))
      const uint32_t xoff = OFF_STG + w * 16384 + wq * 2048 + lane * 16;
      const uint32_t rcv = sbase + OFF_STG + w * 16384;
      const uint32_t col = SEG_IDX(seg) * 256 + SEG_FLAG(seg) * 128, row = SEG_M(seg) * 128 + w * 64 + wq * 16;
      const bool addto = SEG_EPI(seg) == E_FINRED;
      uint4* gp = ptr_add(p.out, ((row + (lane >> 3)) * DM + col + (lane & 7) * 8) * 2);
      const uint32_t lp = rcv + wq * 2048 + (lane >> 3) * 128 + (((lane & 7) ^ (lane >> 3)) << 4);
      if (!full) mbar_wait(fbar, ph);
      wg_fence();
      BETA_BLOCK(0, 0, 0, 1)
      BETA_FULL(1);
      wg_fence();
      BETA_BLOCK(0, 2, 1, 0)
      wg_commit();
      BETA_FULL(2);
      {
        const uint32_t dst = map_peer(sbase + xoff, (b & 1) ^ 1), dbar = map_peer(bars + B_RECV + 8 * w, (b & 1) ^ 1);
        mbar_wait_cluster(bars + B_PEER, 0);
#pragma unroll
        for (int q = 0; q < 8; q++) {
          const int i = 64 + 8 * q;
          asm volatile("st.async.weak.shared::cluster.mbarrier::complete_tx::bytes.v4.b32 [%0], {%1,%2,%3,%4}, [%5];"
                       ::"r"(dst + (q >> 2) * 8192 + (q & 3) * 512), "r"(pack2(d[i], d[i + 1])), "r"(pack2(d[i + 2], d[i + 3])),
                         "r"(pack2(d[i + 4], d[i + 5])), "r"(pack2(d[i + 6], d[i + 7])), "r"(dbar) : "memory");
        }
      }
      wg_wait_lo(d);
      wg_fence();
      BETA_BLOCK(1, 1, 1, 2)
      BETA_BLOCK(2, 0, 2, 1)
      BETA_FULL(3);
      wg_fence();
      BETA_BLOCK(2, 2, 3, 0)
      wg_commit();
      mbar_wait_cluster(bars + B_RECV + 8 * w, 0);
#pragma unroll
      for (int q = 0; q < 8; q++)
        asm volatile("ld.shared.v4.u32 {%0,%1,%2,%3}, [%4];" : "=r"(pk[4 * q]), "=r"(pk[4 * q + 1]), "=r"(pk[4 * q + 2]), "=r"(pk[4 * q + 3])
                     : "r"(rcv + wq * 2048 + lane * 16 + (q >> 2) * 8192 + (q & 3) * 512) : "memory");
      __syncwarp();
      mbar_wait(bars + B_HOK, 0);
      wg_wait_lo(d);
#pragma unroll
      for (int sb = 0; sb < 2; sb++) {
#pragma unroll
        for (int jj = 0; jj < 4; jj++) {
          uint32_t o[4];
#pragma unroll
          for (int r = 0; r < 4; r++) {
            const int i = 32 * sb + 8 * jj + 2 * r;
            o[r] = pack2(d[i] + bf_lo(pk[i >> 1]), d[i + 1] + bf_hi(pk[i >> 1]));
          }
          stsm4((rcv + lane_off + sb * 8192) ^ (jj << 5), o[0], o[1], o[2], o[3]);
        }
        __syncwarp();
#pragma unroll
        for (int q = 0; q < 4; q++) {
          uint32_t v0, v1, v2, v3;
          asm volatile("ld.shared.v4.u32 {%0,%1,%2,%3}, [%4];" : "=r"(v0), "=r"(v1), "=r"(v2), "=r"(v3)
                       : "r"((lp + sb * 8192 + q * 512) ^ ((q & 1) << 6)) : "memory");
          if (addto)
            asm volatile("red.relaxed.gpu.global.add.noftz.v4.bf16x2 [%0], {%1,%2,%3,%4};"
                         ::"l"(gp + sb * 8 + q * 512), "r"(v0), "r"(v1), "r"(v2), "r"(v3) : "memory");
          else
            asm volatile("st.global.v4.u32 [%0], {%1,%2,%3,%4};" ::"l"(gp + sb * 8 + q * 512), "r"(v0), "r"(v1), "r"(v2), "r"(v3) : "memory");
        }
      }
    }
  } else {
    asm volatile("setmaxnreg.dec.sync.aligned.u32 56;");
    if (warp > 2) {
      unsigned ep = 0;
      asm volatile("barrier.sync 1, 384;" ::: "memory");
      asm volatile("barrier.cluster.arrive.relaxed.aligned;" ::: "memory");
      if (lane == 0) {
        asm volatile("ld.relaxed.gpu.global.u32 %0, [%1];" : "=r"(ep) : "l"(&p.sync->epoch[b]) : "memory");
        ep += 1;
        p.sync->epoch[b] = ep;
        asm volatile("st.shared.u32 [%0], %1;" ::"r"(bars + W_EPOCH), "r"(ep) : "memory");
        mbar_arrive(bars + B_EPOCH);
        prefetch_map(&p.xa); prefetch_map(&p.wg); prefetch_map(&p.wu); prefetch_map(&p.zst); prefetch_map(&p.zld);
        prefetch_map(&p.hre); prefetch_map(&p.him); prefetch_map(&p.wd); prefetch_map(&p.outm);
        __nanosleep(3000);
        poll_ge(&p.sync->gatecnt[0], ep * 256);
        mbar_arrive(bars + B_GREADY);
      }
      ep = __shfl_sync(0xffffffff, ep, 0);
      const unsigned target = lane < 2 ? ep * 4 : ep;
      uint32_t ready = 0, cur_m = 99, cnt = 0, published = 0;
      for (int si = 1;; si++) {
        const uint32_t seg = c_sched.s[b][si];
        const uint32_t type = SEG_TYPE(seg), m = SEG_M(seg);
        if (type == T_END) break;
        if (type < T_OUTM) continue;
        if (m != cur_m) { cur_m = m; ready = 0; }
        const unsigned* fp = ptr_add(p.sync->flags, (m * 32 + lane) * 4);
        const uint32_t kend = SEG_K0(seg) + SEG_NK(seg);
        for (uint32_t kb = SEG_K0(seg); kb < kend; kb++) {
          const uint32_t src = kb < 32 ? (kb >> 4) : (kb >> 1) - 14;
          if (!((ready >> src) & 1)) {
            if (cnt != published) {
              published = cnt;
              if (lane == 0) asm volatile("st.release.cta.shared.u32 [%0], %1;" ::"r"(bars + W_CLEAR), "r"(cnt) : "memory");
            }
            uint32_t it = 0;
            while (!((__ballot_sync(0xffffffff, (int)(ld_relaxed(fp) - target) >= 0) >> src) & 1)) {
              __nanosleep(300);
              trap_if(++it > (1u << 22));
            }
            ready = __ballot_sync(0xffffffff, (int)(ld_acquire(fp) - target) >= 0);
            fence_async();
            __syncwarp();
          }
          cnt++;
        }
      }
      if (lane == 0) asm volatile("st.release.cta.shared.u32 [%0], %1;" ::"r"(bars + W_CLEAR), "r"(cnt) : "memory");
    } else if (warp > 0) {
      const uint32_t w = warp - 1;
      const uint32_t stg = sbase + OFF_STG + w * 16384;
      if (warp == 1 && elect_one()) {
#pragma unroll
        for (int s = 0; s < STAGES; s++) mbar_init(bars + B_EMPTY + 8 * s, 8);
#pragma unroll
        for (int s = 0; s < 4; s++) { mbar_init(bars + B_SFULL + 8 * s, 4); mbar_init(bars + B_SEMPTY + 8 * s, 1); }
        mbar_init(bars + B_RECV, 1); mbar_init(bars + B_RECV + 8, 1);
#pragma unroll
        for (int s = 0; s < 10; s++) mbar_init(bars + B_GLOAD + 8 * s, 1);
        asm volatile("st.shared.u32 [%0], %1;" ::"r"(bars + W_CLEAR), "r"(0) : "memory");
        asm volatile("fence.mbarrier_init.release.cluster;" ::: "memory");
        fence_async_smem();
      }
      __syncwarp();
      asm volatile("barrier.sync 1, 384;" ::: "memory");
      asm volatile("barrier.cluster.arrive.relaxed.aligned;" ::: "memory");
      if (b < 128) {
        const int row0 = SEG_M(seg0) * 128 + SEG_IDX(seg0) * 16 + w * 8;
        float zrow = 0.f;
        const uint4* wp = ptr_add(p.gw, lane * 16);
        const uint4* xp = p.x + row0 * 128;
        uint4 wv[4];
#pragma unroll
        for (int i = 0; i < 4; i++) wv[i] = __ldg(wp + i * 32);
        mbar_wait(bars + B_FULL + 8, 0);
#define GATE_LOAD(r)                                                                                               \
  if (lane == 0) {                                                                                                 \
    const uint32_t gb = bars + B_GLOAD + 16 * w + 4 * ((r) & 2);                                                   \
    mbar_expect(gb, 4096);                                                                                         \
    asm volatile("cp.async.bulk.shared::cluster.global.mbarrier::complete_tx::bytes [%0], [%1], 4096, [%2];"      \
                 ::"r"(stg + (r) * 2048), "l"(ptr_add(xp, (r) * 2048)), "r"(gb) : "memory");                       \
  }
        GATE_LOAD(0)
#pragma unroll 1
        for (int r = 0; r < 8; r += 2) {
          mbar_wait(bars + B_GLOAD + 16 * w + 4 * (r & 2), (r >> 2) & 1);
          if (r < 6) GATE_LOAD(r + 2)
          float z0 = 0.f, z1 = 0.f, y0 = 0.f, y1 = 0.f;
#pragma unroll
          for (int i = 0; i < 4; i++) {
            uint32_t a[4], c[4];
            asm volatile("ld.shared.v4.u32 {%0,%1,%2,%3}, [%4];" : "=r"(a[0]), "=r"(a[1]), "=r"(a[2]), "=r"(a[3])
                         : "r"(stg + r * 2048 + i * 512 + lane * 16) : "memory");
            asm volatile("ld.shared.v4.u32 {%0,%1,%2,%3}, [%4+2048];" : "=r"(c[0]), "=r"(c[1]), "=r"(c[2]), "=r"(c[3])
                         : "r"(stg + r * 2048 + i * 512 + lane * 16) : "memory");
            const uint32_t wq4[4] = {wv[i].x, wv[i].y, wv[i].z, wv[i].w};
#pragma unroll
            for (int e = 0; e < 4; e++) {
              const uint32_t pa = mul2(a[e], wq4[e]), pc = mul2(c[e], wq4[e]);
              z0 += bf_lo(pa); z1 += bf_hi(pa);
              y0 += bf_lo(pc); y1 += bf_hi(pc);
            }
          }
          float z = z0 + z1, y = y0 + y1;
          const float keep = lane < 16 ? z : y, give = lane < 16 ? y : z;
          z = keep + __shfl_xor_sync(0xffffffff, give, 16);
#pragma unroll
          for (int o = 8; o > 0; o >>= 1) z += __shfl_xor_sync(0xffffffff, z, o);
          if ((lane & 15) == r + (lane >> 4)) zrow = z;
        }
        const float g = round_bf(rcpf(1.f + expf(-round_bf(zrow))));
        const float ic = rcpf(round_bf(1.f - g));
        if ((lane & 15) < 8 && (lane & 1) == (lane >> 4)) *ptr_add(p.sync->gate, (row0 + (lane & 15)) * 8) = make_float2(g, ic > 1e38f ? 1e38f : ic);
        __syncwarp();
        if (lane == 0) red_release(&p.sync->gatecnt[0]);
      }
      __syncwarp();
      asm volatile("barrier.cluster.wait.aligned;" ::: "memory");
      if (elect_one()) {
        uint32_t ep, fph = 0, mine = w ^ 1, tph = w ^ 1;
        mbar_wait(bars + B_EPOCH, 0);
        asm volatile("ld.shared.u32 %0, [%1];" : "=r"(ep) : "r"(bars + W_EPOCH) : "memory");
        for (int si = 0;; si++) {
          const uint32_t seg = c_sched.s[b][si];
          const uint32_t epi = SEG_EPI(seg), m = SEG_M(seg), idx = SEG_IDX(seg);
          if (SEG_TYPE(seg) == T_END) break;
          if (epi == E_NONE) continue;
          if (epi == E_SEND) {
            if (mine) {
              if (SEG_EPI(c_sched.s[b][si + 1]) == E_FINRED) {
                poll_ge(ptr_add(p.sync->hflag, (m * 4 + idx) * 4), ep);
                fence_async();
              }
              mbar_arrive(bars + B_HOK);
            } else {
              mbar_expect(bars + B_RECV, 16384);
              mbar_expect(bars + B_RECV + 8, 16384);
              mbar_arrive_remote(map_peer(bars + B_PEER, (b & 1) ^ 1));
            }
            break;
          }
          mine ^= 1;
          if (mine) {
            if (epi == E_GU) fph ^= 1;
            continue;
          }
          mbar_wait(bars + B_TURN + 8 * w, tph);
          tph ^= 1;
          if (SEG_TYPE(c_sched.s[b][si + 1]) == T_END) {
            mbar_wait(bars + B_SFULL, fph);
            mbar_wait(bars + B_SFULL + 16, fph);
            red_release(ptr_add(p.sync->flags, (512 + m * 4 + idx) * 4));
            break;
          }
          const uint32_t nsb = epi == E_GU ? 2 : 4;
          uint32_t row, flag;
          if (epi == E_PQ) { row = (m * KZ + idx * 4) * 128; flag = m * 32 + (idx >> 2); }
          else if (epi == E_GU) { row = (m * KZ + 32 + idx * 2) * 128; flag = m * 32 + 2 + idx; }
          else { row = m * 128; flag = 512 + m * 4 + idx; }
#pragma unroll 1
          for (uint32_t sb = 0; sb < nsb; sb++) {
            const uint32_t buf = sb & 1;
#pragma unroll 1
            for (uint32_t g = 0; g < 2; g++) {
              const uint32_t src = sbase + OFF_STG + g * 16384 + buf * 8192;
              mbar_wait(bars + B_SFULL + g * 16 + 8 * buf, fph);
              if (epi == E_HELP) {
#pragma unroll
                for (int q = 0; q < 4; q++) tma_store(&p.outm, src + q * 2048, idx * 256 + sb * 64, row + g * 64 + q * 16);
              } else {
                tma_store(&p.zst, src, 0, row + sb * 128 + g * 64);
              }
            }
            bulk_commit();
            bulk_wait_read();
            mbar_arrive(bars + B_SEMPTY + 8 * buf);
            mbar_arrive(bars + B_SEMPTY + 16 + 8 * buf);
            fph ^= buf;
          }
          mbar_arrive(bars + B_TURN + 8 * (w ^ 1));
          bulk_wait();
          red_release(ptr_add(p.sync->flags, flag * 4));
        }
      }
    } else {
      if (elect_one()) {
#pragma unroll
        for (int s = 1; s < STAGES; s++) mbar_init(bars + B_FULL + 8 * s, 1);
        asm volatile("fence.mbarrier_init.release.cluster;" ::: "memory");
      }
      __syncwarp();
      asm volatile("barrier.arrive 1, 384;" ::: "memory");
      if (elect_one()) {
        const First f = first_loads(b);
#pragma unroll 1
        for (int s = 1; s < STAGES; s++) {
          FIRST_LOADS(s)
        }
      }
      __syncwarp();
      asm volatile("barrier.cluster.arrive.relaxed.aligned;" ::: "memory");
      asm volatile("barrier.cluster.wait.aligned;" ::: "memory");
      if (elect_one()) {
        uint32_t seg = seg0 + (STAGES << 12) - (STAGES << 19);
        uint32_t st = 0, ph = 0, cnt = 0, cleared = 0;
#define WAIT_CLEARED()                                                                                            \
  {                                                                                                               \
    uint32_t it = 0;                                                                                              \
    while (cleared <= cnt) {                                                                                      \
      asm volatile("ld.acquire.cta.shared.u32 %0, [%1];" : "=r"(cleared) : "r"(bars + W_CLEAR) : "memory");     \
      trap_if(++it > (1u << 26));                                                                                 \
    }                                                                                                             \
    cnt++;                                                                                                        \
  }
        for (int si = 1; SEG_TYPE(seg) != T_END; si++) {
          const uint32_t type = SEG_TYPE(seg);
          int nk = SEG_NK(seg);
          Loads l = seg_loads(p, seg);
          if (type == T_OUTB) {
#pragma unroll 1
            for (int slot = 0; slot < 12; slot += 3) {
              mbar_wait(bars + B_EMPTY + 8 * st, ph);
              const uint32_t fb = bars + B_FULL + 8 * st;
              mbar_expect(fb, slot < 9 ? ST_BYTES : 16384);
#pragma unroll 1
              for (int r = 0; r < 3 && slot + r < 2 * NBETA; r++) {
                const uint32_t dst = sbase + st * ST_BYTES + r * 16384;
                if ((slot + r) & 1) { tma3d(dst, l.mb0, 0, l.b1, l.c0, fb); l.b1 += 64; }
                else { WAIT_CLEARED(); tma2d(dst, l.ma, 0, l.a1, fb); l.a1 += 128; }
              }
              if (++st == STAGES) { st = 0; ph ^= 1; }
            }
            break;
          }
#pragma unroll 1
          for (; nk > 0; nk--) {
            if (type >= T_OUTM) WAIT_CLEARED();
            mbar_wait(bars + B_EMPTY + 8 * st, ph);
            issue_loads(l, sbase + st * ST_BYTES, bars + B_FULL + 8 * st, type == T_GU && SEG_FLAG(seg) && nk > 16 - STAGES);
            if (++st == STAGES) { st = 0; ph ^= 1; }
          }
          seg = c_sched.s[b][si];
        }
      }
    }
  }
}

struct FbArgs { const __nv_bfloat16 *x, *sre, *sim, *hre, *him, *wg, *wu, *wd, *gw; __nv_bfloat16 *z, *out; };
__global__ void fallback_kernel(FbArgs a, int mode) {
  __shared__ float sa[32][33], sb[32][33], sc[32][33];
  const int tx = threadIdx.x, ty = threadIdx.y, r = blockIdx.y * 32 + ty, c0 = blockIdx.x * 32, c = c0 + tx;
  const int K = mode == 0 ? SEQ : mode == 1 ? DM : KZ * 64;
  float acc = 0.f, acc2 = 0.f;
  for (int k0 = 0; k0 < K; k0 += 32) {
    if (mode == 0) {
      sa[ty][tx] = __bfloat162float((c0 < DM ? a.sre : a.sim)[r * SEQ + k0 + tx]);
      sb[ty][tx] = __bfloat162float(a.x[(k0 + ty) * DM + (c & (DM - 1))]);
    } else if (mode == 1) {
      sa[ty][tx] = __bfloat162float(a.x[r * DM + k0 + tx]);
      sb[ty][tx] = __bfloat162float(a.wg[(k0 + ty) * FF + c]);
      sc[ty][tx] = __bfloat162float(a.wu[(k0 + ty) * FF + c]);
    } else {
      sa[ty][tx] = __bfloat162float(a.z[r * (KZ * 64) + k0 + tx]);
      if (k0 < 2 * DM) sb[tx][ty] = __bfloat162float((k0 < DM ? a.hre : a.him)[(c0 + ty) * DM + (k0 & (DM - 1)) + tx]);
      else sb[ty][tx] = __bfloat162float(a.wd[(k0 - 2 * DM + ty) * DM + c]);
    }
    __syncthreads();
    for (int k = 0; k < 32; k++) {
      acc = fmaf(sa[ty][k], sb[k][tx], acc);
      if (mode == 1) acc2 = fmaf(sa[ty][k], sc[k][tx], acc2);
    }
    __syncthreads();
  }
  if (mode == 2) { a.out[r * DM + c] = __float2bfloat16(acc); return; }
  float z = 0.f;
  for (int k = tx; k < DM; k += 32) z += round_bf(__bfloat162float(a.x[r * DM + k]) * __bfloat162float(a.gw[k]));
  for (int o = 16; o > 0; o >>= 1) z += __shfl_xor_sync(0xffffffff, z, o);
  const float g = round_bf(1.f / (1.f + expf(-round_bf(z))));
  if (mode == 0) a.z[r * (KZ * 64) + c] = __float2bfloat16((c0 < DM ? acc : -acc) * g);
  else a.z[r * (KZ * 64) + 2 * DM + c] = __float2bfloat16(acc2 / (1.f + expf(-acc)) * round_bf(1.f - g));
}

typedef CUresult (*EncodeFn)(CUtensorMap*, CUtensorMapDataType, cuuint32_t, void*, const cuuint64_t*, const cuuint64_t*,
                             const cuuint32_t*, const cuuint32_t*, CUtensorMapInterleave, CUtensorMapSwizzle,
                             CUtensorMapL2promotion, CUtensorMapFloatOOBfill);

constexpr CUtensorMapL2promotion L2PROM = CU_TENSOR_MAP_L2_PROMOTION_L2_128B;

void map2d(EncodeFn enc, CUtensorMap* m, const void* ptr, uint64_t inner, uint64_t outer, uint32_t rows, bool swz) {
  cuuint64_t dims[2] = {inner, outer}, str[1] = {inner * 2};
  cuuint32_t box[2] = {64, rows}, es[2] = {1, 1};
  enc(m, CU_TENSOR_MAP_DATA_TYPE_BFLOAT16, 2, (void*)ptr, dims, str, box, es, CU_TENSOR_MAP_INTERLEAVE_NONE,
      swz ? CU_TENSOR_MAP_SWIZZLE_128B : CU_TENSOR_MAP_SWIZZLE_NONE, L2PROM, CU_TENSOR_MAP_FLOAT_OOB_FILL_NONE);
}
void map3k(EncodeFn enc, CUtensorMap* m, const void* ptr, uint64_t K, uint64_t N) {
  cuuint64_t dims[3] = {K, N, 1}, str[2] = {K * 2, K * N * 2};
  cuuint32_t box[3] = {64, 128, 1}, es[3] = {1, 1, 1};
  enc(m, CU_TENSOR_MAP_DATA_TYPE_BFLOAT16, 3, (void*)ptr, dims, str, box, es, CU_TENSOR_MAP_INTERLEAVE_NONE,
      CU_TENSOR_MAP_SWIZZLE_128B, L2PROM, CU_TENSOR_MAP_FLOAT_OOB_FILL_NONE);
}
void map3d(EncodeFn enc, CUtensorMap* m, const void* ptr, uint64_t N, uint64_t K, uint32_t chunks) {
  cuuint64_t dims[3] = {64, K, N / 64}, str[2] = {N * 2, 128};
  cuuint32_t box[3] = {64, 64, chunks}, es[3] = {1, 1, 1};
  enc(m, CU_TENSOR_MAP_DATA_TYPE_BFLOAT16, 3, (void*)ptr, dims, str, box, es, CU_TENSOR_MAP_INTERLEAVE_NONE,
      CU_TENSOR_MAP_SWIZZLE_128B, L2PROM, CU_TENSOR_MAP_FLOAT_OOB_FILL_NONE);
}

}

extern "C" void kernel_launch(void* const* d_in, const int* in_sizes, int n_in, void* d_out, int out_size) {
  (void)in_sizes; (void)n_in; (void)out_size;
  EncodeFn enc = nullptr;
  cudaDriverEntryPointQueryResult q;
  cudaGetDriverEntryPoint("cuTensorMapEncodeTiled", (void**)&enc, cudaEnableDefault, &q);
  void *z = nullptr, *sy = nullptr;
  cudaGetSymbolAddress(&z, g_Z);
  cudaGetSymbolAddress(&sy, g_sync);
  cudaFuncSetAttribute(fused_kernel, cudaFuncAttributeMaxDynamicSharedMemorySize, SMEM_BYTES);
  cudaLaunchConfig_t cfg = {};
  cfg.gridDim = dim3(NCTA); cfg.blockDim = dim3(384); cfg.dynamicSmemBytes = SMEM_BYTES;
  cudaLaunchAttribute at;
  at.id = cudaLaunchAttributeClusterDimension;
  at.val.clusterDim.x = 2; at.val.clusterDim.y = 1; at.val.clusterDim.z = 1;
  cfg.attrs = &at; cfg.numAttrs = 1;
  int nclusters = 0;
  cudaOccupancyMaxActiveClusters(&nclusters, fused_kernel, &cfg);
  if (nclusters < NCTA / 2 || !enc) {
    typedef const __nv_bfloat16* P;
    const FbArgs a = {(P)d_in[0], (P)d_in[1], (P)d_in[2], (P)d_in[3], (P)d_in[4], (P)d_in[6], (P)d_in[7], (P)d_in[8],
                      (P)d_in[9], (__nv_bfloat16*)z, (__nv_bfloat16*)d_out};
    fallback_kernel<<<dim3(2 * DM / 32, SEQ / 32), dim3(32, 32)>>>(a, 0);
    fallback_kernel<<<dim3(FF / 32, SEQ / 32), dim3(32, 32)>>>(a, 1);
    fallback_kernel<<<dim3(DM / 32, SEQ / 32), dim3(32, 32)>>>(a, 2);
    return;
  }
  Params p;
  map2d(enc, &p.sre, d_in[1], SEQ, SEQ, 128, true);
  map2d(enc, &p.sim, d_in[2], SEQ, SEQ, 128, true);
  map2d(enc, &p.xa, d_in[0], DM, SEQ, 128, true);
  map3d(enc, &p.xb, d_in[0], DM, SEQ, 2);
  map3d(enc, &p.wg, d_in[6], FF, DM, 2);
  map3d(enc, &p.wu, d_in[7], FF, DM, 2);
  map3k(enc, &p.hre, d_in[3], DM, DM);
  map3k(enc, &p.him, d_in[4], DM, DM);
  map3d(enc, &p.wd, d_in[8], DM, FF, 2);
  map2d(enc, &p.zld, z, 64, ZROWS, 128, false);
  map2d(enc, &p.zst, z, 64, ZROWS, 64, false);
  map2d(enc, &p.outm, d_out, DM, SEQ, 16, true);
  p.x = (const uint4*)d_in[0];
  p.gw = (const uint4*)d_in[9];
  p.sync = (Sync*)sy;
  p.out = (uint4*)d_out;
  for (int b = 0; b < NCTA; b++) p.first[b] = first_seg(b);
  fused_kernel<<<NCTA, 384, SMEM_BYTES>>>(p);
}
```
